```python
import torch

def _softmax(x, axis=-1):
    return torch.softmax(x, dim=axis)
def _gelu(x):
    return torch.nn.functional.gelu(x, approximate="tanh")
def _silu(x):
    return torch.nn.functional.silu(x)
def _sigmoid(x):
    return torch.sigmoid(x)
def _layernorm(x, axis=-1, eps=1e-5):
    m = x.mean(dim=axis, keepdim=True)
    v = x.var(dim=axis, keepdim=True, unbiased=False)
    return (x - m) / torch.sqrt(v + eps)
def _scatter_add(tgt, idx, src, axis=0):
    return tgt.clone().index_add_(axis, idx, src)
def _segment_sum(src, seg, n):
    out = torch.zeros((n,) + src.shape[1:], dtype=src.dtype)
    return out.index_add_(0, seg, src)
def _pad(x, pw):
    flat = tuple(v for pair in reversed(pw) for v in pair)
    return torch.nn.functional.pad(x, flat)

kernel_name = 'sequential_preLN__linear_kernel_hedgehog__glu_gated_reglu__prompt'

def setup_inputs():

    _w = (lambda a: (lambda t: t.to(torch.bfloat16) if t.is_floating_point() else t)(torch.as_tensor(a)))
    def _A_setup():
        B, S, D, H = 1, 2048, 512, 32
        Dh = D // H
        return {
            "x": _w((lambda *s: torch.randn(*s, dtype=torch.bfloat16) * 0.05)(B, S, D)),
            "wqkv": _w((lambda *s: torch.randn(*s, dtype=torch.bfloat16) * 0.2)(D, 3 * D)),
            "w_phi": _w((lambda *s: torch.randn(*s, dtype=torch.bfloat16) * 0.2)(H, Dh, Dh) * (Dh ** -0.5)),
            "wo": _w((lambda *s: torch.randn(*s, dtype=torch.bfloat16) * 0.05)(D, D)),
        }
    _A_in = _A_setup()

    def _B_setup():
        B, S, D, F = 1, 2048, 512, 1792
        return {
            "x": _w((lambda *s: torch.randn(*s, dtype=torch.bfloat16) * 0.05)(B, S, D)),
            "W_gate": _w((lambda *s: torch.randn(*s, dtype=torch.bfloat16) * 0.4)(D, F) * (2.0 / D) ** 0.5),
            "W_up": _w((lambda *s: torch.randn(*s, dtype=torch.bfloat16) * 0.4)(D, F) * (2.0 / D) ** 0.5),
            "W_down": _w((lambda *s: torch.randn(*s, dtype=torch.bfloat16) * 0.4)(F, D) * (1.0 / F) ** 0.5),
        }
    _B_in = _B_setup()

    return {
        "A_x": _A_in["x"],
        "A_wqkv": _A_in["wqkv"],
        "A_w_phi": _A_in["w_phi"],
        "A_wo": _A_in["wo"],
        "B_x": _B_in["x"],
        "B_W_gate": _B_in["W_gate"],
        "B_W_up": _B_in["W_up"],
        "B_W_down": _B_in["W_down"],
    }

def reference(A_x, A_wqkv, A_w_phi, A_wo, B_x, B_W_gate, B_W_up, B_W_down):
    def _A_ref(x, wqkv, w_phi, wo):
        B, S, D = x.shape
        H = 32; Dh = D // H
        qkv = (lambda x, *d: x.permute(*d))((x @ wqkv).reshape(B, S, 3, H, Dh), 2, 0, 3, 1, 4)
        q, k, v = qkv[0], qkv[1], qkv[2]
        pq = torch.einsum("bhsd,hdf->bhsf", q, w_phi)
        pk = torch.einsum("bhsd,hdf->bhsf", k, w_phi)
        phi_q = torch.concatenate([_softmax(pq, axis=-1), _softmax(-pq, axis=-1)], axis=-1)
        phi_k = torch.concatenate([_softmax(pk, axis=-1), _softmax(-pk, axis=-1)], axis=-1)
        kv = torch.einsum("bhsf,bhsd->bhfd", phi_k, v)
        z  = torch.einsum("bhsf->bhf", phi_k)
        num = torch.einsum("bhqf,bhfd->bhqd", phi_q, kv)
        den = torch.einsum("bhqf,bhf->bhq", phi_q, z)[..., None] + 1e-6
        o = num / den
        return (lambda x, *d: x.permute(*d))(o, 0, 2, 1, 3).reshape(B, S, D) @ wo

    def _B_ref(x, W_gate, W_up, W_down):
        gate = torch.einsum("bsd,df->bsf", x, W_gate)
        up = torch.einsum("bsd,df->bsf", x, W_up)
        gate = gate * (lambda x, dt: x.to(dt))(gate > 0, gate.dtype)
        h = gate * up
        return torch.einsum("bsf,fd->bsd", h, W_down)

    x = A_x
    h = x + _A_ref(_layernorm(x, axis=-1), A_wqkv, A_w_phi, A_wo)
    h2 = h + _B_ref(_layernorm(h, axis=-1), B_W_gate, B_W_up, B_W_down)
    return h2
```

```cpp
#include <cuda_runtime.h>
#include <cuda_bf16.h>
#include <cuda.h>
#include <stdint.h>

template <uint32_t HB, int TB> __device__ __forceinline__ void wgmma_n256_rs(float (&d)[128], uint32_t a0, uint32_t a1, uint32_t a2, uint32_t a3, uint32_t db, int sc) {
  asm volatile("{\n.reg .pred p;\n.reg .b64 db;\nsetp.ne.b32 p, %133, 0;\nmov.b64 db, {%132, %135};\n"
    "wgmma.mma_async.sync.aligned.m64n256k16.f32.bf16.bf16 {%0, %1, %2, %3, %4, %5, %6, %7, %8, %9, %10, %11, %12, %13, %14, %15, %16, %17, %18, %19, %20, %21, %22, %23, %24, %25, %26, %27, %28, %29, %30, %31, %32, %33, %34, %35, %36, %37, %38, %39, %40, %41, %42, %43, %44, %45, %46, %47, %48, %49, %50, %51, %52, %53, %54, %55, %56, %57, %58, %59, %60, %61, %62, %63, %64, %65, %66, %67, %68, %69, %70, %71, %72, %73, %74, %75, %76, %77, %78, %79, %80, %81, %82, %83, %84, %85, %86, %87, %88, %89, %90, %91, %92, %93, %94, %95, %96, %97, %98, %99, %100, %101, %102, %103, %104, %105, %106, %107, %108, %109, %110, %111, %112, %113, %114, %115, %116, %117, %118, %119, %120, %121, %122, %123, %124, %125, %126, %127}, {%128, %129, %130, %131}, db, p, 1, 1, %134;\n}\n"
    : "+f"(d[0]), "+f"(d[1]), "+f"(d[2]), "+f"(d[3]), "+f"(d[4]), "+f"(d[5]), "+f"(d[6]), "+f"(d[7]), "+f"(d[8]), "+f"(d[9]), "+f"(d[10]), "+f"(d[11]), "+f"(d[12]), "+f"(d[13]), "+f"(d[14]), "+f"(d[15]), "+f"(d[16]), "+f"(d[17]), "+f"(d[18]), "+f"(d[19]), "+f"(d[20]), "+f"(d[21]), "+f"(d[22]), "+f"(d[23]), "+f"(d[24]), "+f"(d[25]), "+f"(d[26]), "+f"(d[27]), "+f"(d[28]), "+f"(d[29]), "+f"(d[30]), "+f"(d[31]), "+f"(d[32]), "+f"(d[33]), "+f"(d[34]), "+f"(d[35]), "+f"(d[36]), "+f"(d[37]), "+f"(d[38]), "+f"(d[39]), "+f"(d[40]), "+f"(d[41]), "+f"(d[42]), "+f"(d[43]), "+f"(d[44]), "+f"(d[45]), "+f"(d[46]), "+f"(d[47]), "+f"(d[48]), "+f"(d[49]), "+f"(d[50]), "+f"(d[51]), "+f"(d[52]), "+f"(d[53]), "+f"(d[54]), "+f"(d[55]), "+f"(d[56]), "+f"(d[57]), "+f"(d[58]), "+f"(d[59]), "+f"(d[60]), "+f"(d[61]), "+f"(d[62]), "+f"(d[63]), "+f"(d[64]), "+f"(d[65]), "+f"(d[66]), "+f"(d[67]), "+f"(d[68]), "+f"(d[69]), "+f"(d[70]), "+f"(d[71]), "+f"(d[72]), "+f"(d[73]), "+f"(d[74]), "+f"(d[75]), "+f"(d[76]), "+f"(d[77]), "+f"(d[78]), "+f"(d[79]), "+f"(d[80]), "+f"(d[81]), "+f"(d[82]), "+f"(d[83]), "+f"(d[84]), "+f"(d[85]), "+f"(d[86]), "+f"(d[87]), "+f"(d[88]), "+f"(d[89]), "+f"(d[90]), "+f"(d[91]), "+f"(d[92]), "+f"(d[93]), "+f"(d[94]), "+f"(d[95]), "+f"(d[96]), "+f"(d[97]), "+f"(d[98]), "+f"(d[99]), "+f"(d[100]), "+f"(d[101]), "+f"(d[102]), "+f"(d[103]), "+f"(d[104]), "+f"(d[105]), "+f"(d[106]), "+f"(d[107]), "+f"(d[108]), "+f"(d[109]), "+f"(d[110]), "+f"(d[111]), "+f"(d[112]), "+f"(d[113]), "+f"(d[114]), "+f"(d[115]), "+f"(d[116]), "+f"(d[117]), "+f"(d[118]), "+f"(d[119]), "+f"(d[120]), "+f"(d[121]), "+f"(d[122]), "+f"(d[123]), "+f"(d[124]), "+f"(d[125]), "+f"(d[126]), "+f"(d[127])
    : "r"(a0), "r"(a1), "r"(a2), "r"(a3), "r"(db), "r"(sc), "n"(TB), "n"(HB));
}
template <uint32_t HA, uint32_t HB, int TA, int TB> __device__ __forceinline__ void wgmma_n192_ss(float (&d)[96], uint32_t da, uint32_t db, int sc) {
  asm volatile("{\n.reg .pred p;\n.reg .b64 da, db;\nsetp.ne.b32 p, %98, 0;\nmov.b64 da, {%96, %101};\nmov.b64 db, {%97, %102};\n"
    "wgmma.mma_async.sync.aligned.m64n192k16.f32.bf16.bf16 {%0, %1, %2, %3, %4, %5, %6, %7, %8, %9, %10, %11, %12, %13, %14, %15, %16, %17, %18, %19, %20, %21, %22, %23, %24, %25, %26, %27, %28, %29, %30, %31, %32, %33, %34, %35, %36, %37, %38, %39, %40, %41, %42, %43, %44, %45, %46, %47, %48, %49, %50, %51, %52, %53, %54, %55, %56, %57, %58, %59, %60, %61, %62, %63, %64, %65, %66, %67, %68, %69, %70, %71, %72, %73, %74, %75, %76, %77, %78, %79, %80, %81, %82, %83, %84, %85, %86, %87, %88, %89, %90, %91, %92, %93, %94, %95}, da, db, p, 1, 1, %99, %100;\n}\n"
    : "+f"(d[0]), "+f"(d[1]), "+f"(d[2]), "+f"(d[3]), "+f"(d[4]), "+f"(d[5]), "+f"(d[6]), "+f"(d[7]), "+f"(d[8]), "+f"(d[9]), "+f"(d[10]), "+f"(d[11]), "+f"(d[12]), "+f"(d[13]), "+f"(d[14]), "+f"(d[15]), "+f"(d[16]), "+f"(d[17]), "+f"(d[18]), "+f"(d[19]), "+f"(d[20]), "+f"(d[21]), "+f"(d[22]), "+f"(d[23]), "+f"(d[24]), "+f"(d[25]), "+f"(d[26]), "+f"(d[27]), "+f"(d[28]), "+f"(d[29]), "+f"(d[30]), "+f"(d[31]), "+f"(d[32]), "+f"(d[33]), "+f"(d[34]), "+f"(d[35]), "+f"(d[36]), "+f"(d[37]), "+f"(d[38]), "+f"(d[39]), "+f"(d[40]), "+f"(d[41]), "+f"(d[42]), "+f"(d[43]), "+f"(d[44]), "+f"(d[45]), "+f"(d[46]), "+f"(d[47]), "+f"(d[48]), "+f"(d[49]), "+f"(d[50]), "+f"(d[51]), "+f"(d[52]), "+f"(d[53]), "+f"(d[54]), "+f"(d[55]), "+f"(d[56]), "+f"(d[57]), "+f"(d[58]), "+f"(d[59]), "+f"(d[60]), "+f"(d[61]), "+f"(d[62]), "+f"(d[63]), "+f"(d[64]), "+f"(d[65]), "+f"(d[66]), "+f"(d[67]), "+f"(d[68]), "+f"(d[69]), "+f"(d[70]), "+f"(d[71]), "+f"(d[72]), "+f"(d[73]), "+f"(d[74]), "+f"(d[75]), "+f"(d[76]), "+f"(d[77]), "+f"(d[78]), "+f"(d[79]), "+f"(d[80]), "+f"(d[81]), "+f"(d[82]), "+f"(d[83]), "+f"(d[84]), "+f"(d[85]), "+f"(d[86]), "+f"(d[87]), "+f"(d[88]), "+f"(d[89]), "+f"(d[90]), "+f"(d[91]), "+f"(d[92]), "+f"(d[93]), "+f"(d[94]), "+f"(d[95])
    : "r"(da), "r"(db), "r"(sc), "n"(TA), "n"(TB), "n"(HA), "n"(HB));
}
template <uint32_t HB, int TB> __device__ __forceinline__ void wgmma_n64_rs(float (&d)[32], uint32_t a0, uint32_t a1, uint32_t a2, uint32_t a3, uint32_t db, int sc) {
  asm volatile("{\n.reg .pred p;\n.reg .b64 db;\nsetp.ne.b32 p, %37, 0;\nmov.b64 db, {%36, %39};\n"
    "wgmma.mma_async.sync.aligned.m64n64k16.f32.bf16.bf16 {%0, %1, %2, %3, %4, %5, %6, %7, %8, %9, %10, %11, %12, %13, %14, %15, %16, %17, %18, %19, %20, %21, %22, %23, %24, %25, %26, %27, %28, %29, %30, %31}, {%32, %33, %34, %35}, db, p, 1, 1, %38;\n}\n"
    : "+f"(d[0]), "+f"(d[1]), "+f"(d[2]), "+f"(d[3]), "+f"(d[4]), "+f"(d[5]), "+f"(d[6]), "+f"(d[7]), "+f"(d[8]), "+f"(d[9]), "+f"(d[10]), "+f"(d[11]), "+f"(d[12]), "+f"(d[13]), "+f"(d[14]), "+f"(d[15]), "+f"(d[16]), "+f"(d[17]), "+f"(d[18]), "+f"(d[19]), "+f"(d[20]), "+f"(d[21]), "+f"(d[22]), "+f"(d[23]), "+f"(d[24]), "+f"(d[25]), "+f"(d[26]), "+f"(d[27]), "+f"(d[28]), "+f"(d[29]), "+f"(d[30]), "+f"(d[31])
    : "r"(a0), "r"(a1), "r"(a2), "r"(a3), "r"(db), "r"(sc), "n"(TB), "n"(HB));
}
template <uint32_t HA, uint32_t HB, int TA, int TB> __device__ __forceinline__ void wgmma_n40_ss(float (&d)[20], uint32_t da, uint32_t db, int sc) {
  asm volatile("{\n.reg .pred p;\n.reg .b64 da, db;\nsetp.ne.b32 p, %22, 0;\nmov.b64 da, {%20, %25};\nmov.b64 db, {%21, %26};\n"
    "wgmma.mma_async.sync.aligned.m64n40k16.f32.bf16.bf16 {%0, %1, %2, %3, %4, %5, %6, %7, %8, %9, %10, %11, %12, %13, %14, %15, %16, %17, %18, %19}, da, db, p, 1, 1, %23, %24;\n}\n"
    : "+f"(d[0]), "+f"(d[1]), "+f"(d[2]), "+f"(d[3]), "+f"(d[4]), "+f"(d[5]), "+f"(d[6]), "+f"(d[7]), "+f"(d[8]), "+f"(d[9]), "+f"(d[10]), "+f"(d[11]), "+f"(d[12]), "+f"(d[13]), "+f"(d[14]), "+f"(d[15]), "+f"(d[16]), "+f"(d[17]), "+f"(d[18]), "+f"(d[19])
    : "r"(da), "r"(db), "r"(sc), "n"(TA), "n"(TB), "n"(HA), "n"(HB));
}

namespace {

constexpr int SEQ = 2048, DM = 512, FF = 1792;
constexpr int SPIN_LIMIT = 1 << 16;

struct Scratch {
  __align__(1024) unsigned epoch[132 * 8];
  __align__(1024) uint4 cs[384 + 128];
  __align__(1024) uint4 xs[2048 * 2];
  __align__(1024) uint4 kv2[8 * 320];
  __align__(1024) uint4 mu[16 * 64 * 4];
  __align__(1024) uint4 ss[16 * 64 * 4];
  __align__(1024) uint4 kv1[8 * 17 * 16 * 32];
  __align__(1024) uint4 o[16 * 32 * 256];
  __align__(1024) uint4 h[16 * 32 * 256];
  __align__(1024) uint4 part[128 * 1024];
};
__device__ Scratch g_scratch;
#define TS(n)
#define TSINIT
#define TSDUMP
#define TSA(n)
#define TSG(n)
#define TSR(k, n)
#define DBG(x)

constexpr uint32_t SB0 = 1024;
constexpr uint32_t RING_OFF = 131072, SLOT = 16384;
constexpr uint32_t SMALL_OFF = RING_OFF + 6 * SLOT;
constexpr uint32_t BAR_FULL = SMALL_OFF, BAR_EMPTY = BAR_FULL + 48;
constexpr uint32_t BAR_X = BAR_EMPTY + 48, BAR_W = BAR_X + 64, BAR_WE = BAR_W + 64;
constexpr uint32_t BAR_WO = BAR_WE + 32, BAR_AUX = BAR_WO + 8, BAR_AUXQ = BAR_AUX + 8, BAR_KV = BAR_AUXQ + 8;
constexpr uint32_t BAR_G = BAR_KV + 8, BAR_STAGE = BAR_G + 8, BAR_WODONE = BAR_STAGE + 8;
constexpr uint32_t BAR_PFREE = BAR_WODONE + 8, BAR_ACTA = BAR_PFREE + 16, BAR_ACTB = BAR_ACTA + 16, BAR_PFREE2 = BAR_ACTB + 16;
constexpr uint32_t WSLOT = 24576;
constexpr uint32_t CS_OFF = SMALL_OFF + 512;
constexpr uint32_t ONES_OFF = SMALL_OFF + 1536;
constexpr uint32_t SMEM_BYTES = 232448;
constexpr uint32_t V_OFF = 2 * 16384, TAB_OFF = 3 * 16384, WO_OFF = 4 * 16384;
constexpr uint32_t WBAR_OFF = SMALL_OFF + 2560;

__device__ __forceinline__ void mbar_init(uint32_t b, uint32_t c) { asm volatile("mbarrier.init.shared::cta.b64 [%0], %1;" ::"r"(b), "r"(c) : "memory"); }
__device__ __forceinline__ void mbar_expect(uint32_t b, uint32_t bytes) { asm volatile("mbarrier.arrive.expect_tx.shared::cta.b64 _, [%0], %1;" ::"r"(b), "r"(bytes) : "memory"); }
__device__ __forceinline__ void mbar_arrive(uint32_t b) { asm volatile("mbarrier.arrive.shared::cta.b64 _, [%0];" ::"r"(b) : "memory"); }
__device__ __forceinline__ void mbar_arrive_remote(uint32_t b) { asm volatile("mbarrier.arrive.shared::cluster.b64 _, [%0];" ::"r"(b) : "memory"); }
__device__ __forceinline__ void mbar_wait(uint32_t b, uint32_t ph) {
  asm volatile("{\n.reg .pred p;\n.reg .u32 c;\nmov.u32 c, 0;\n"
               "W: mbarrier.try_wait.parity.shared::cta.b64 p, [%0], %1;\n@p bra D;\n"
               "add.u32 c, c, 1;\nsetp.lt.u32 p, c, 262144;\n@p bra W;\nD:\n}" ::"r"(b), "r"(ph) : "memory");
}
__device__ __forceinline__ void mbar_wait_cluster(uint32_t b, uint32_t ph) {
  asm volatile("{\n.reg .pred p;\n.reg .u32 c;\nmov.u32 c, 0;\n"
               "W: mbarrier.try_wait.parity.acquire.cluster.shared::cta.b64 p, [%0], %1;\n@p bra D;\n"
               "add.u32 c, c, 1;\nsetp.lt.u32 p, c, 262144;\n@p bra W;\nD:\n}" ::"r"(b), "r"(ph) : "memory");
}
__device__ __forceinline__ void tma2(uint32_t dst, const CUtensorMap* m, int c0, int c1, uint32_t bar) {
  asm volatile("cp.async.bulk.tensor.2d.shared::cluster.global.mbarrier::complete_tx::bytes [%0], [%1, {%3, %4}], [%2];" ::"r"(dst), "l"(m), "r"(bar), "r"(c0), "r"(c1) : "memory");
}
__device__ __forceinline__ void tma3(uint32_t dst, const CUtensorMap* m, int c0, int c1, int c2, uint32_t bar) {
  asm volatile("cp.async.bulk.tensor.3d.shared::cluster.global.mbarrier::complete_tx::bytes [%0], [%1, {%3, %4, %5}], [%2];" ::"r"(dst), "l"(m), "r"(bar), "r"(c0), "r"(c1), "r"(c2) : "memory");
}
__device__ __forceinline__ void l2_prefetch(const void* p, uint32_t bytes) { asm volatile("cp.async.bulk.prefetch.L2.global [%0], %1;" ::"l"(p), "r"(bytes) : "memory"); }
__device__ __forceinline__ uint4 ld_rlx(const uint4* p) {
  uint4 v;
  asm volatile("{\n.reg .b128 r;\n.reg .b64 a, b;\nld.relaxed.gpu.global.b128 r, [%4];\nmov.b128 {a, b}, r;\nmov.b64 {%0, %1}, a;\nmov.b64 {%2, %3}, b;\n}"
               : "=r"(v.x), "=r"(v.y), "=r"(v.z), "=r"(v.w) : "l"(p) : "memory");
  return v;
}
__device__ __forceinline__ uint2 ld_rlx2(const uint2* p) { uint2 v; asm volatile("ld.relaxed.gpu.global.v2.u32 {%0,%1}, [%2];" : "=r"(v.x), "=r"(v.y) : "l"(p) : "memory"); return v; }
__device__ __forceinline__ uint32_t ld_rlx1(const unsigned* p) { uint32_t v; asm volatile("ld.relaxed.gpu.global.u32 %0, [%1];" : "=r"(v) : "l"(p) : "memory"); return v; }
__device__ __forceinline__ void st_rlx(uint4* p, uint32_t a, uint32_t b, uint32_t c, uint32_t d) {
  asm volatile("st.relaxed.gpu.global.v4.u32 [%0], {%1, %2, %3, %4};" ::"l"(p), "r"(a), "r"(b), "r"(c), "r"(d) : "memory");
}
__device__ __forceinline__ void st_rlx2(void* p, uint32_t a, uint32_t b) { asm volatile("st.relaxed.gpu.global.v2.u32 [%0], {%1,%2};" ::"l"(p), "r"(a), "r"(b) : "memory"); }
__device__ __forceinline__ void st_rlx1(void* p, uint32_t a) { asm volatile("st.relaxed.gpu.global.u32 [%0], %1;" ::"l"(p), "r"(a) : "memory"); }
__device__ __forceinline__ void fence_async() { asm volatile("fence.proxy.async.shared::cta;" ::: "memory"); }
__device__ __forceinline__ void bar_sync(int id, int n) { asm volatile("bar.sync %0, %1;" ::"r"(id), "r"(n) : "memory"); }
__device__ __forceinline__ void bar_arrive(int id, int n) { asm volatile("bar.arrive %0, %1;" ::"r"(id), "r"(n) : "memory"); }
__device__ __forceinline__ uint32_t tagw(uint32_t w, uint32_t tag) { return (w & ~1u) | tag; }
__device__ __forceinline__ uint32_t tagf(float f, uint32_t tag) { return (__float_as_uint(f) & ~1u) | tag; }
__device__ __forceinline__ uint32_t bad2(uint32_t a, uint32_t b, uint32_t tag) {
  uint32_t r; asm("lop3.b32 %0, %1, %2, %3, 0x7E;" : "=r"(r) : "r"(a), "r"(b), "r"(tag)); return r;
}
__device__ __forceinline__ uint32_t or3(uint32_t a, uint32_t b, uint32_t c) { uint32_t r; asm("lop3.b32 %0, %1, %2, %3, 0xFE;" : "=r"(r) : "r"(a), "r"(b), "r"(c)); return r; }
__device__ __forceinline__ bool any_bad(uint32_t m) { return __any_sync(~0u, m & 1u); }
__device__ __forceinline__ float round15(float f) { return __uint_as_float((__float_as_uint(f) + 0x10000u) & 0xFFFE0000u); }
__device__ __forceinline__ float round_odd(float f) { return __uint_as_float((__float_as_uint(f) & 0xFFFE0000u) | 0x10000u); }
__device__ __forceinline__ float untag(uint32_t w) { return __uint_as_float(w & ~1u); }
__device__ __forceinline__ uint32_t pack(float lo, float hi) { uint32_t r; asm("cvt.rn.bf16x2.f32 %0, %1, %2;" : "=r"(r) : "f"(hi), "f"(lo)); return r; }
__device__ __forceinline__ uint32_t reglu(float g0, float g1, float u0, float u1) {
  uint32_t r;
  asm("{\n.reg .b32 a, b;\ncvt.rn.relu.bf16x2.f32 a, %2, %1;\ncvt.rn.bf16x2.f32 b, %4, %3;\nmul.rn.bf16x2 %0, a, b;\n}" : "=r"(r) : "f"(g0), "f"(g1), "f"(u0), "f"(u1));
  return r;
}
__device__ __forceinline__ uint32_t add2(uint32_t a, uint32_t b) { uint32_t r; asm("add.rn.bf16x2 %0, %1, %2;" : "=r"(r) : "r"(a), "r"(b)); return r; }
__device__ __forceinline__ uint32_t mul2(uint32_t a, uint32_t b) { uint32_t r; asm("mul.rn.bf16x2 %0, %1, %2;" : "=r"(r) : "r"(a), "r"(b)); return r; }
__device__ __forceinline__ uint32_t max2(uint32_t a, uint32_t b) { uint32_t r; asm("max.bf16x2 %0, %1, %2;" : "=r"(r) : "r"(a), "r"(b)); return r; }
__device__ __forceinline__ uint32_t min2(uint32_t a, uint32_t b) { uint32_t r; asm("min.bf16x2 %0, %1, %2;" : "=r"(r) : "r"(a), "r"(b)); return r; }
__device__ __forceinline__ float blo(uint32_t v) { return __uint_as_float(v << 16); }
__device__ __forceinline__ float bhi(uint32_t v) { return __uint_as_float(v & 0xFFFF0000u); }
__device__ __forceinline__ float ex2(float x) { float r; asm("ex2.approx.ftz.f32 %0, %1;" : "=f"(r) : "f"(x)); return r; }
__device__ __forceinline__ float rcp(float x) { float r; asm("rcp.approx.ftz.f32 %0, %1;" : "=f"(r) : "f"(x)); return r; }
__device__ __forceinline__ void ldsm4(uint32_t addr, uint32_t& a, uint32_t& b, uint32_t& c, uint32_t& d) {
  asm volatile("ldmatrix.sync.aligned.m8n8.x4.shared.b16 {%0,%1,%2,%3}, [%4];" : "=r"(a), "=r"(b), "=r"(c), "=r"(d) : "r"(addr) : "memory");
}
__device__ __forceinline__ void stsm4(uint32_t addr, uint32_t a, uint32_t b, uint32_t c, uint32_t d) {
  asm volatile("stmatrix.sync.aligned.m8n8.x4.shared.b16 [%0], {%1,%2,%3,%4};" ::"r"(addr), "r"(a), "r"(b), "r"(c), "r"(d) : "memory");
}
__device__ __forceinline__ uint4 lds4(uint32_t a) { uint4 v; asm volatile("ld.shared.v4.u32 {%0,%1,%2,%3}, [%4];" : "=r"(v.x), "=r"(v.y), "=r"(v.z), "=r"(v.w) : "r"(a) : "memory"); return v; }
__device__ __forceinline__ uint2 lds2(uint32_t a) { uint2 v; asm volatile("ld.shared.v2.u32 {%0,%1}, [%2];" : "=r"(v.x), "=r"(v.y) : "r"(a) : "memory"); return v; }
__device__ __forceinline__ void sts4(uint32_t a, const uint4& v) { asm volatile("st.shared.v4.u32 [%0], {%1,%2,%3,%4};" ::"r"(a), "r"(v.x), "r"(v.y), "r"(v.z), "r"(v.w) : "memory"); }
__device__ __forceinline__ void st_async4(uint32_t addr, uint32_t a, uint32_t b, uint32_t c, uint32_t d, uint32_t bar) {
  asm volatile("st.async.shared::cluster.mbarrier::complete_tx::bytes.v4.b32 [%0], {%1,%2,%3,%4}, [%5];" ::"r"(addr), "r"(a), "r"(b), "r"(c), "r"(d), "r"(bar) : "memory");
}
__device__ __forceinline__ void hmma(float& c0, float& c1, float& c2, float& c3, uint32_t a0, uint32_t a1, uint32_t a2, uint32_t a3, uint32_t b0, uint32_t b1) {
  asm("mma.sync.aligned.m16n8k16.row.col.f32.bf16.bf16.f32 {%0,%1,%2,%3}, {%4,%5,%6,%7}, {%8,%9}, {%0,%1,%2,%3};"
      : "+f"(c0), "+f"(c1), "+f"(c2), "+f"(c3) : "r"(a0), "r"(a1), "r"(a2), "r"(a3), "r"(b0), "r"(b1));
}
__device__ __forceinline__ uint32_t movm(uint32_t a) { uint32_t r; asm volatile("movmatrix.sync.aligned.m8n8.trans.b16 %0, %1;" : "=r"(r) : "r"(a)); return r; }
__device__ __forceinline__ uint32_t clock32() { uint32_t c; asm volatile("mov.u32 %0, %clock;" : "=r"(c)); return c; }
__device__ __forceinline__ void delay(uint32_t clks) { const uint32_t t0 = clock32(); while (clock32() - t0 < clks) {} }
__device__ __forceinline__ bool elect_one() {
  uint32_t p;
  asm volatile("{\n.reg .pred p;\nelect.sync _|p, 0xffffffff;\nselp.u32 %0, 1, 0, p;\n}" : "=r"(p));
  return p;
}
__device__ __forceinline__ void wg_fence() { asm volatile("wgmma.fence.sync.aligned;" ::: "memory"); }
__device__ __forceinline__ void wg_commit() { asm volatile("wgmma.commit_group.sync.aligned;" ::: "memory"); }
template <int N> __device__ __forceinline__ void wg_wait() { asm volatile("wgmma.wait_group.sync.aligned %0;" ::"n"(N) : "memory"); }
template <int N> __device__ __forceinline__ void pin(float (&d)[N]) {
#pragma unroll
  for (int i = 0; i < N; i++) asm volatile("" : "+f"(d[i])::"memory");
}
template <class T> __device__ __forceinline__ void pinp(T*& p) { asm volatile("" : "+l"(p)::"memory"); }
__device__ __forceinline__ void pinf(float& a) { asm volatile("" : "+f"(a)::"memory"); }
__device__ __forceinline__ void pinu(uint32_t& a) { asm volatile("" : "+r"(a)::"memory"); }
__host__ __device__ constexpr uint32_t dlo(uint32_t addr, uint32_t lbo) { return (addr >> 4) | ((lbo >> 4) << 16); }
constexpr uint32_t H128 = (1024 >> 4) | (1u << 30), H64 = (512 >> 4) | (2u << 30);
__host__ __device__ constexpr int ring_pos(int n) { return n % 6; }
__host__ __device__ constexpr int ring_par(int n) { return (n / 6) & 1; }
constexpr unsigned long long DOWN_PART = 0x3210321032130210ull, DOWN_CHUNK = 0x3333222211101000ull;
__host__ __device__ constexpr uint32_t dslot(int n) { return SB0 + RING_OFF + ring_pos(n) * SLOT; }

__device__ __forceinline__ uint32_t idle_mma() {
  uint32_t r;
  asm volatile("{\n.reg .f32 a, b, c, d;\n.reg .b32 z;\nmov.b32 z, 0;\nmov.f32 a, 0f00000000;\n"
               "mma.sync.aligned.m16n8k16.row.col.f32.bf16.bf16.f32 {a, b, c, d}, {z, z, z, z}, {z, z}, {a, a, a, a};\nmov.b32 %0, a;\n}" : "=r"(r));
  return r;
}
__device__ __forceinline__ void warm_wait(uint32_t b) {
  uint32_t ok;
  int spin = 0;
  do {
    spin += idle_mma();
    asm volatile("{\n.reg .pred p;\nmbarrier.test_wait.parity.shared::cta.b64 p, [%1], 0;\nselp.u32 %0, 1, 0, p;\n}" : "=r"(ok) : "r"(b) : "memory");
  } while (!__all_sync(~0u, ok) && ++spin < 262144);
}
__device__ __forceinline__ float idle_pass(float v) {
  asm volatile("{\n.reg .f32 b, c, d;\n.reg .b32 z;\nmov.b32 z, 0;\n"
               "mma.sync.aligned.m16n8k16.row.col.f32.bf16.bf16.f32 {%0, b, c, d}, {z, z, z, z}, {z, z}, {%0, %0, %0, %0};\n}" : "+f"(v));
  return v;
}
template <int N> __device__ __forceinline__ void ldn(uint4 (&v)[N], const uint4* p) {
#pragma unroll
  for (int k = 0; k < N; k++) v[k] = ld_rlx(p + k * 256);
}
struct Tag { uint32_t v, zero; };
__device__ __forceinline__ void verify4(uint4 (&v)[4], const uint4* p, Tag tag) {
  asm volatile("{\n.reg .pred p;\n.reg .b32 m, c;\n.reg .b128 r;\n.reg .b64 a, b;\nmov.u32 c, %18;\nsetp.ne.u32 p, c, 0;\n"
               "L:\n"
               "mov.b64 a, {%0, %1};\nmov.b64 b, {%2, %3};\nmov.b128 r, {a, b};\n@p ld.relaxed.gpu.global.b128 r, [%16 + 0];\nmov.b128 {a, b}, r;\nmov.b64 {%0, %1}, a;\nmov.b64 {%2, %3}, b;\n"
               "mov.b64 a, {%4, %5};\nmov.b64 b, {%6, %7};\nmov.b128 r, {a, b};\n@p ld.relaxed.gpu.global.b128 r, [%16 + 4096];\nmov.b128 {a, b}, r;\nmov.b64 {%4, %5}, a;\nmov.b64 {%6, %7}, b;\n"
               "mov.b64 a, {%8, %9};\nmov.b64 b, {%10, %11};\nmov.b128 r, {a, b};\n@p ld.relaxed.gpu.global.b128 r, [%16 + 8192];\nmov.b128 {a, b}, r;\nmov.b64 {%8, %9}, a;\nmov.b64 {%10, %11}, b;\n"
               "mov.b64 a, {%12, %13};\nmov.b64 b, {%14, %15};\nmov.b128 r, {a, b};\n@p ld.relaxed.gpu.global.b128 r, [%16 + 12288];\nmov.b128 {a, b}, r;\nmov.b64 {%12, %13}, a;\nmov.b64 {%14, %15}, b;\n"
               "xor.b32 m, %0, %17;\n"
               "lop3.b32 m, m, %4, %17, 0xF6;\n"
               "lop3.b32 m, m, %8, %17, 0xF6;\n"
               "lop3.b32 m, m, %12, %17, 0xF6;\n"
               "and.b32 m, m, 1;\nsetp.ne.u32 p, m, 0;\nvote.sync.any.pred p, p, 0xffffffff;\nadd.u32 c, c, 1;\nsetp.lt.and.u32 p, c, 65536, p;\n@p bra L;\n"
               "}"
               : "+r"(v[0].x), "+r"(v[0].y), "+r"(v[0].z), "+r"(v[0].w), "+r"(v[1].x), "+r"(v[1].y), "+r"(v[1].z), "+r"(v[1].w), "+r"(v[2].x), "+r"(v[2].y), "+r"(v[2].z), "+r"(v[2].w), "+r"(v[3].x), "+r"(v[3].y), "+r"(v[3].z), "+r"(v[3].w)
               : "l"(p), "r"(tag.v), "r"(tag.zero) : "memory");
}
__device__ __forceinline__ void verify1(uint4 (&v)[1], const uint4* p, Tag tag) {
  asm volatile("{\n.reg .pred p;\n.reg .b32 m, c;\n.reg .b128 r;\n.reg .b64 a, b;\nmov.u32 c, %6;\nsetp.ne.u32 p, c, 0;\n"
               "L:\n"
               "mov.b64 a, {%0, %1};\nmov.b64 b, {%2, %3};\nmov.b128 r, {a, b};\n@p ld.relaxed.gpu.global.b128 r, [%4 + 0];\nmov.b128 {a, b}, r;\nmov.b64 {%0, %1}, a;\nmov.b64 {%2, %3}, b;\n"
               "xor.b32 m, %0, %5;\n"
               "and.b32 m, m, 1;\nsetp.ne.u32 p, m, 0;\nvote.sync.any.pred p, p, 0xffffffff;\nadd.u32 c, c, 1;\nsetp.lt.and.u32 p, c, 65536, p;\n@p bra L;\n"
               "and.b32 %0, %0, 0xFFFFFFFE;\n"
               "}"
               : "+r"(v[0].x), "+r"(v[0].y), "+r"(v[0].z), "+r"(v[0].w)
               : "l"(p), "r"(tag.v), "r"(tag.zero) : "memory");
}
template <int OFF> __device__ __forceinline__ void verify6(uint4 (&v)[6], const uint4* const (&p)[3], Tag tag) {
  asm volatile("{\n.reg .pred p;\n.reg .b32 m, c;\n.reg .b128 r;\n.reg .b64 a, b;\nmov.u32 c, %28;\nsetp.ne.u32 p, c, 0;\n"
               "L:\n"
               "mov.b64 a, {%0, %1};\nmov.b64 b, {%2, %3};\nmov.b128 r, {a, b};\n@p ld.relaxed.gpu.global.b128 r, [%24 + %29];\nmov.b128 {a, b}, r;\nmov.b64 {%0, %1}, a;\nmov.b64 {%2, %3}, b;\n"
               "mov.b64 a, {%4, %5};\nmov.b64 b, {%6, %7};\nmov.b128 r, {a, b};\n@p ld.relaxed.gpu.global.b128 r, [%25 + %29];\nmov.b128 {a, b}, r;\nmov.b64 {%4, %5}, a;\nmov.b64 {%6, %7}, b;\n"
               "mov.b64 a, {%8, %9};\nmov.b64 b, {%10, %11};\nmov.b128 r, {a, b};\n@p ld.relaxed.gpu.global.b128 r, [%26 + %29];\nmov.b128 {a, b}, r;\nmov.b64 {%8, %9}, a;\nmov.b64 {%10, %11}, b;\n"
               "mov.b64 a, {%12, %13};\nmov.b64 b, {%14, %15};\nmov.b128 r, {a, b};\n@p ld.relaxed.gpu.global.b128 r, [%24 + %30];\nmov.b128 {a, b}, r;\nmov.b64 {%12, %13}, a;\nmov.b64 {%14, %15}, b;\n"
               "mov.b64 a, {%16, %17};\nmov.b64 b, {%18, %19};\nmov.b128 r, {a, b};\n@p ld.relaxed.gpu.global.b128 r, [%25 + %30];\nmov.b128 {a, b}, r;\nmov.b64 {%16, %17}, a;\nmov.b64 {%18, %19}, b;\n"
               "mov.b64 a, {%20, %21};\nmov.b64 b, {%22, %23};\nmov.b128 r, {a, b};\n@p ld.relaxed.gpu.global.b128 r, [%26 + %30];\nmov.b128 {a, b}, r;\nmov.b64 {%20, %21}, a;\nmov.b64 {%22, %23}, b;\n"
               "xor.b32 m, %0, %27;\n"
               "lop3.b32 m, m, %4, %27, 0xF6;\n"
               "lop3.b32 m, m, %8, %27, 0xF6;\n"
               "lop3.b32 m, m, %12, %27, 0xF6;\n"
               "lop3.b32 m, m, %16, %27, 0xF6;\n"
               "lop3.b32 m, m, %20, %27, 0xF6;\n"
               "and.b32 m, m, 1;\nsetp.ne.u32 p, m, 0;\nvote.sync.any.pred p, p, 0xffffffff;\nadd.u32 c, c, 1;\nsetp.lt.and.u32 p, c, 65536, p;\n@p bra L;\n"
               "}"
               : "+r"(v[0].x), "+r"(v[0].y), "+r"(v[0].z), "+r"(v[0].w), "+r"(v[1].x), "+r"(v[1].y), "+r"(v[1].z), "+r"(v[1].w), "+r"(v[2].x), "+r"(v[2].y), "+r"(v[2].z), "+r"(v[2].w), "+r"(v[3].x), "+r"(v[3].y), "+r"(v[3].z), "+r"(v[3].w), "+r"(v[4].x), "+r"(v[4].y), "+r"(v[4].z), "+r"(v[4].w), "+r"(v[5].x), "+r"(v[5].y), "+r"(v[5].z), "+r"(v[5].w)
               : "l"(p[0]), "l"(p[1]), "l"(p[2]), "r"(tag.v), "r"(tag.zero), "n"(OFF), "n"(OFF + 4096) : "memory");
}
template <int OFF> __device__ __forceinline__ void verify2x2(uint2& u, uint2& v, const uint2* p, Tag tag) {
  asm volatile("{\n.reg .pred p;\n.reg .b32 m, c;\nmov.u32 c, %6;\nsetp.ne.u32 p, c, 0;\nL:\n"
               "@p ld.relaxed.gpu.global.v2.u32 {%0, %1}, [%4];\n@p ld.relaxed.gpu.global.v2.u32 {%2, %3}, [%4 + %7];\n"
               "xor.b32 m, %0, %5;\nlop3.b32 m, m, %1, %5, 0xF6;\nlop3.b32 m, m, %2, %5, 0xF6;\nlop3.b32 m, m, %3, %5, 0xF6;\n"
               "and.b32 m, m, 1;\nsetp.ne.u32 p, m, 0;\nvote.sync.any.pred p, p, 0xffffffff;\nadd.u32 c, c, 1;\nsetp.lt.and.u32 p, c, 65536, p;\n@p bra L;\n}"
               : "+r"(u.x), "+r"(u.y), "+r"(v.x), "+r"(v.y) : "l"(p), "r"(tag.v), "r"(tag.zero), "n"(OFF) : "memory");
}
__device__ __forceinline__ void light_poll(const uint4* p, bool active, Tag tag, uint32_t first) {
  asm volatile("{\n.reg .pred p, q;\n.reg .b32 m, c;\nmov.u32 c, %4;\nsetp.ne.u32 q, %2, 0;\nsetp.ne.u32 p, c, 0;\nL:\nand.pred p, p, q;\n@p ld.relaxed.gpu.global.u32 %0, [%1];\n"
               "xor.b32 m, %0, %3;\nand.b32 m, m, 1;\nsetp.ne.and.u32 p, m, 0, q;\nvote.sync.any.pred p, p, 0xffffffff;\nadd.u32 c, c, 1;\nsetp.lt.and.u32 p, c, 65536, p;\n@p bra L;\n}"
               : "+r"(first) : "l"(p), "r"((uint32_t)active), "r"(tag.v), "r"(tag.zero) : "memory");
}

__device__ __forceinline__ uint32_t role_of(uint32_t c) {
  const uint32_t u = c - 36, q = (u * 37) >> 8;
  const uint32_t gpc = c < 4 ? 8 : c < 36 ? (c - 4) & 7 : 1 + (u - 7 * q), slot = c < 4 ? c : c < 36 ? (c - 4) >> 3 : 4 + q;
  const uint32_t bi = gpc == 0 || gpc >= 7 ? 12 + (slot & 3) : 4 * ((gpc - 1) >> 1) + (slot & 3);
  const uint32_t bp = gpc == 0 ? 2 : gpc == 8 ? 3 : gpc == 7 ? slot >> 2 : 2 * ((gpc - 1) & 1) + (slot >> 2);
  return 8 * bi + 2 * bp;
}

struct Params {
  CUtensorMap x, wqkv, wsum, wo, wgA, wuA, wgB, wuB, wd128, wd96;
  const __nv_bfloat16 *px, *pwqkv, *pwphi, *pwo, *pwg, *pwu, *pwd;
  __nv_bfloat16* out;
  Scratch* s;
  uint32_t always;
};

__global__ void __cluster_dims__(2, 1, 1) __launch_bounds__(384, 1) fused_block_kernel(const __grid_constant__ Params P) {
  extern __shared__ __align__(1024) uint8_t smem_raw[];
  const uint32_t sb = (uint32_t)__cvta_generic_to_shared(smem_raw);
  if ((sb & 0x3FFFF) != SB0) return;
  const uint32_t tid = threadIdx.x, warp = __shfl_sync(~0u, tid >> 5, 0), lane = tid & 31;
  if (blockIdx.x >= 128) {
    const uint32_t hx = blockIdx.x - 128, bar = sb + SMALL_OFF;
    DBG(const long long thx = clock64());
    const bool lead = elect_one();
    if (lead) { mbar_init(bar + 8 * warp, 1); mbar_init(bar + 96 + 8 * warp, 8); }
    __syncthreads();
    if (warp >= 8) {
      if (warp == 8 && lead) {
        uint32_t p = 0, par = 1;
#pragma unroll 1
        for (uint32_t n = 0; n < 32; n++) {
          mbar_wait(bar + 96 + 8 * p, par);
          mbar_expect(bar + 8 * p, 16384);
          if (n < 24) tma3(sb + p * 16384, &P.wsum, 0, 64 * (n & 7), (n < 16 ? 8 + (n & 8) : 0) + 2 * hx, bar + 8 * p);
          else { tma2(sb + p * 16384, &P.wo, 64 * (n & 7), 128 * hx, bar + 8 * p); tma2(sb + p * 16384 + 8192, &P.wo, 64 * (n & 7), 128 * hx + 64, bar + 8 * p); }
          if (++p == 12) { p = 0; par ^= 1; }
        }
      }
      return;
    }
    const uint32_t epoch = ld_rlx1(P.s->epoch + blockIdx.x * 8), tag = (epoch + 1) & 1, l7 = lane & 7;
    uint4* dst = P.s->cs + 32 * hx + 4 * warp + (lane & 1) * 2 + ((lane >> 1) & 1);
    if (lane < 4) {
#pragma unroll
      for (int k = 0; k < 4; k++) st_rlx(dst + 128 * k, tag ^ 1, 0, 0, 0);
    }
    uint32_t p = 0, par = 0;
#pragma unroll 1
    for (uint32_t job = 0; job < 4; job++) {
      float c[8];
#pragma unroll
      for (int k = 0; k < 8; k++) c[k] = 0.f;
#pragma unroll 1
      for (uint32_t n = 0; n < 8; n++) {
        mbar_wait(bar + 8 * p, par);
        uint32_t r[4][4];
        if (job < 3) {
          const uint32_t a = sb + p * 16384 + (warp >> 2) * 8192 + (lane & 15) * 128 + ((((warp & 3) * 2 + (lane >> 4)) ^ l7) << 4);
#pragma unroll
          for (int k = 0; k < 4; k++)
            asm volatile("ldmatrix.sync.aligned.m8n8.x4.trans.shared.b16 {%0,%1,%2,%3}, [%4];" : "=r"(r[k][0]), "=r"(r[k][1]), "=r"(r[k][2]), "=r"(r[k][3]) : "r"(a + k * 2048) : "memory");
        } else {
          const uint32_t a = sb + p * 16384 + warp * 2048 + (l7 + 8 * (lane >> 4)) * 128, sw = (((lane >> 3) & 1) ^ l7) << 4;
#pragma unroll
          for (int k = 0; k < 4; k++) ldsm4(a + (sw ^ (k * 32)), r[k][0], r[k][1], r[k][2], r[k][3]);
        }
        if (lane == 0) mbar_arrive(bar + 96 + 8 * p);
        if (++p == 12) { p = 0; par ^= 1; }
        const uint32_t one = 0x3F803F80u;
#pragma unroll
        for (int k = 0; k < 4; k++) {
          hmma(c[0], c[1], c[2], c[3], one, one, one, one, r[k][0], r[k][1]);
          hmma(c[4], c[5], c[6], c[7], one, one, one, one, r[k][2], r[k][3]);
        }
      }
      const bool odd = lane & 1;
      const float sc = job == 3 ? 1.f / DM : 1.f;
      const float u0 = __shfl_xor_sync(~0u, odd ? c[0] : c[4], 1), u1 = __shfl_xor_sync(~0u, odd ? c[1] : c[5], 1);
      DBG(if (tid == 0) g_ring[128 * 5 * 64 - 32 + hx * 4 + job] = clock64() - thx);
      if (lane < 4) st_rlx(dst + 128 * (job == 2 ? 0 : job == 3 ? 3 : job + 1), tagf((odd ? u0 : c[0]) * sc, tag), __float_as_uint((odd ? u1 : c[1]) * sc),
                           __float_as_uint((odd ? c[4] : u0) * sc), __float_as_uint((odd ? c[5] : u1) * sc));
    }
    bar_sync(1, 256);
    if (tid == 0) st_rlx1(P.s->epoch + blockIdx.x * 8, epoch + 1);
    return;
  }
  const uint32_t br = blockIdx.x & 1, b = role_of(blockIdx.x >> 1) + br, bi = b >> 3, bj = b & 7, bp = bj >> 1;
  const uint32_t bc = 4 * br + bp;
  TSINIT;
  TS(0);

  auto xperm = [&](uint32_t s) { return s == 0 ? bc : s - (s <= bc); };

  auto load_x = [&](uint32_t n) { mbar_expect(sb + BAR_X + 8 * n, 16384); tma2(sb + n * 16384, &P.x, 64 * n, 128 * bi, sb + BAR_X + 8 * n); };
  auto load_w = [&](uint32_t n) { mbar_expect(sb + BAR_W + 8 * n, WSLOT); tma3(sb + RING_OFF + (n & 3) * WSLOT, &P.wqkv, 64 * bj, 64 * n, 0, sb + BAR_W + 8 * n); };
  auto touch = [&](uint32_t c) {
    const uint32_t e = lane - 16;
    const __nv_bfloat16* p = lane < 16 ? P.px + (16 * b + lane) * DM + 64 * c : P.pwqkv + (64 * c + 4 * bi + (e & 3)) * (3 * DM) + (e >> 2) * DM + 64 * bj;
    if (lane < 28) asm volatile("prefetch.global.L2 [%0];" ::"l"(p));
  };
  if (warp == 11) touch(0);
  if (elect_one()) {
    const uint32_t cnt = (uint32_t)((warp < 4 ? 0x1111888888111111ull : warp < 8 ? 0x8888111111111111ull : 0x1441111448881111ull) >> (16 * (warp & 3)));
#pragma unroll
    for (uint32_t k = 0; k < 4; k++) mbar_init(sb + BAR_FULL + 32 * warp + 8 * k, (cnt >> (4 * k)) & 15);
    if (warp == 3) load_x(0);
    if (warp == 5) load_w(0);
    asm volatile("fence.mbarrier_init.release.cluster;" ::: "memory");
  }
  __syncwarp();
  auto cta_sync = [&]() { bar_sync(0, 384); asm volatile("barrier.cluster.arrive.relaxed.aligned;" ::: "memory"); };

  if (warp >= 8) {
    asm volatile("setmaxnreg.dec.sync.aligned.u32 56;");
    if (warp == 8) {
      cta_sync();
      if (elect_one()) {
#pragma unroll 1
        for (uint32_t n = 1; n < 8; n++) { load_x(n); if (n < 4) load_w(n); }
        DBG(g_ts[(blockIdx.x * 3 + 2) * 32 + 13] = clock64());
        mbar_expect(sb + BAR_ACTA, 16384); mbar_expect(sb + BAR_ACTA + 8, 16384);
        mbar_expect(sb + BAR_ACTB, 12288); mbar_expect(sb + BAR_ACTB + 8, 12288);
#pragma unroll 1
        for (uint32_t n = 0; n < 4; n++) {
          mbar_wait(sb + BAR_WE + 8 * n, 0);
          load_w(n + 4);
        }
        DBG(int pn = 0);
        int pos = 0, par = 1;
        auto acquire = [&](uint32_t bytes, uint32_t& dst, uint32_t& fb) {
          fb = sb + BAR_FULL + 8 * pos; dst = sb + RING_OFF + pos * SLOT;
          mbar_wait(fb + (BAR_EMPTY - BAR_FULL), par);
          TSR(0, pn); DBG(pn++);
          mbar_expect(fb, bytes);
          if (++pos == 6) { pos = 0; par ^= 1; }
        };
        uint32_t dst, fb;
        mbar_wait(sb + BAR_G, 0);
        mbar_expect(sb + BAR_WO, 65536);
#pragma unroll 1
        for (int m = 0; m < 8; m++) tma2(sb + WO_OFF + m * 8192, &P.wo, 64 * (bc ^ (m & 4) ^ 4), 64 * ((bj + 2 * m) & 7), sb + BAR_WO);
#pragma unroll 1
        for (int s = 0; s < 16; s++) {
          const int kr = xperm(s >> 1) * 64 + (s & 1) * 32;
          if (s == 4) mbar_wait(sb + BAR_KV, 0);
          if (s == 0) { l2_prefetch(P.pwg + b * 4 * FF, 4 * FF * 2); l2_prefetch(P.pwu + b * 4 * FF, 4 * FF * 2); }
          acquire(16384, dst, fb);
          tma3(dst, &P.wgA, 0, kr, 7 * bp + 5 * br, fb);
          tma3(dst + 8192, &P.wuA, 0, kr, 7 * bp + 5 * br, fb);
        }
#pragma unroll 1
        for (int s = 0; s < 16; s++) {
          const int kr = xperm(s >> 1) * 64 + (s & 1) * 32;
          acquire(12288, dst, fb);
          tma3(dst, &P.wgB, 0, kr, 14 * bp + 4 + 3 * br, fb);
          tma3(dst + 6144, &P.wuB, 0, kr, 14 * bp + 4 + 3 * br, fb);
        }
#pragma unroll 1
        for (int tl = 0; tl < 16; tl++) {
          const int part = (int)((DOWN_PART >> (4 * tl)) & 3), ch = (int)((DOWN_CHUNK >> (4 * tl)) & 3);
          const int rr = br ^ (part & 1), r = 448 * bp + (part < 2 ? 320 * rr : 128 + 96 * rr);
          const uint32_t bytes = part < 2 ? 16384 : 12288;
          if (tl >= 6 && tl < 10) { fb = sb + BAR_X + 8 * (tl - 2); dst = sb + (tl - 2) * 16384; mbar_expect(fb, bytes); }
          else acquire(bytes, dst, fb);
          tma2(dst, part < 2 ? &P.wd128 : &P.wd96, 64 * (4 * br + (bp ^ (3 - ch))), r, fb);
        }
      }
    } else {
      const uint32_t aw = warp - 9;
      const uint32_t epoch = ld_rlx1(P.s->epoch + b * 8);
      cta_sync();
      if (aw == 2) { delay(200); touch(1); }
      const uint32_t tag = (epoch + 1) & 1;
      uint4 av[8];
      if (aw == 0) {
#pragma unroll 1
        for (uint32_t e = 0; e < 17; e++) st_rlx(P.s->kv1 + ((bj * 17 + e) * 16 + bi) * 32 + lane, 0, 0, 0, 0);
        __syncwarp();
        if (lane == 0) mbar_arrive(sb + BAR_AUX);
      } else {
        const uint32_t row = 16 * bj + 8 * (aw - 1) + (lane >> 2), rd = sb + row * 128 + (lane & 3) * 32;
        uint2* dst = reinterpret_cast<uint2*>(P.s->xs + 2 * (128 * bi + row)) + (lane & 3);
        st_rlx2(dst, tag ^ 1, tag ^ 1);
        float sa = 0.f, sc = 0.f, qa = 0.f, qc = 0.f;
#pragma unroll 1
        for (uint32_t c = 0; c < 8; c += 4) {
          mbar_wait(sb + BAR_X + 8 * (c + (lane & 3)), 0);
          __syncwarp();
#pragma unroll
          for (int k = 0; k < 8; k++) av[k] = lds4(rd + (c + (k >> 1)) * 16384 + (((k ^ row) & 1) << 4));
#pragma unroll
          for (int k = 0; k < 8; k++) {
            const uint32_t* w = &av[k].x;
#pragma unroll
            for (int q = 0; q < 4; q++) { const float u = blo(w[q]), z = bhi(w[q]); sa += u; sc += z; qa = fmaf(u, u, qa); qc = fmaf(z, z, qc); }
          }
        }
        sa += sc; qa += qc;
#pragma unroll
        for (int o = 1; o <= 2; o <<= 1) { sa += __shfl_xor_sync(~0u, sa, o); qa += __shfl_xor_sync(~0u, qa, o); }
        const float mu = sa * (1.f / DM), rs = rsqrtf(fmaxf(qa * (1.f / DM) - mu * mu, 0.f) + 1e-5f);
        st_rlx2(dst, tagf(mu, tag), tagf(rs, tag));
        TSA(1);
      }
      auto gather16 = [&](const uint4* src, int step, uint32_t want, uint32_t mask, float (&f)[4]) {
        int spin = 0;
        bool bad;
        do {
#pragma unroll
          for (int k = 0; k < 8; k++) av[k] = ld_rlx(src + k * step);
          bad = __any_sync(~0u, ((bad2(av[0].x, av[1].x, want) | bad2(av[2].x, av[3].x, want)) | (bad2(av[4].x, av[5].x, want) | bad2(av[6].x, av[7].x, want))) & mask);
        } while (bad && ++spin < SPIN_LIMIT);
#pragma unroll
        for (int k = 0; k < 8; k++) av[k].x &= ~mask;
#define SUM8(c) (((__uint_as_float(av[0].c) + __uint_as_float(av[1].c)) + (__uint_as_float(av[2].c) + __uint_as_float(av[3].c))) + \
                 ((__uint_as_float(av[4].c) + __uint_as_float(av[5].c)) + (__uint_as_float(av[6].c) + __uint_as_float(av[7].c))))
        f[0] = SUM8(x); f[1] = SUM8(y); f[2] = SUM8(z); f[3] = SUM8(w);
#undef SUM8
#pragma unroll
        for (int k = 0; k < 4; k++) f[k] += __shfl_xor_sync(~0u, f[k], 16);
      };
      const uint4* rec = P.s->kv1 + (bj * 17 + bi) * 16 * 32;
      uint4* kv2 = P.s->kv2 + bj * 320;
      const uint32_t tag2 = tag + 1;
      if (aw < 2) {
        const uint4* src = rec + (lane >> 4) * 8 * 32 + aw * 16 + (lane & 15);
        uint4* dst = kv2 + bi * 16 + aw * 8 + ((lane >> 3) & 1) * 4 + (lane & 3);
        if ((lane & 20) == 0) st_rlx(dst, tag ^ 1, 0, 0, 0);
        mbar_wait(sb + BAR_STAGE, 0);
        TSA(4);
        delay(350);
        TSA(7);
        float f[4];
        gather16(src, 32, tag2, 3, f);
        TSA(8);
        const uint32_t w0 = pack(f[0], f[1]), w1 = pack(f[2], f[3]);
        const uint32_t p0 = __shfl_xor_sync(~0u, w0, 4), p1 = __shfl_xor_sync(~0u, w1, 4);
        if ((lane & 20) == 0) st_rlx(dst, tagw(pack(round15(f[0]), f[1]), tag), p0, w1, p1);
        TSA(5);
      } else {
        const uint2* src = reinterpret_cast<const uint2*>(P.s->kv1 + ((bj * 17 + 16) * 16 + (lane & 12)) * 32) + 4 * bi + (lane & 3);
        uint2* dst = reinterpret_cast<uint2*>(kv2 + 256 + bi * 4) + lane;
        if (lane < 8) st_rlx2(dst, tag ^ 1, tag ^ 1);
        mbar_wait(sb + BAR_STAGE, 0);
        if (lane == 0) st_rlx1(P.s->epoch + b * 8, epoch + 1);
        delay(350);
        int spin = 0;
        bool bad;
        uint2 u[4];
        do {
#pragma unroll
          for (int k = 0; k < 4; k++) u[k] = ld_rlx2(src + k * 64);
          bad = __any_sync(~0u, ((bad2(u[0].x, u[0].y, tag2) | bad2(u[1].x, u[1].y, tag2)) | (bad2(u[2].x, u[2].y, tag2) | bad2(u[3].x, u[3].y, tag2))) & 3);
        } while (bad && ++spin < SPIN_LIMIT);
        TSA(8);
        float z0 = (__uint_as_float(u[0].x & ~3u) + __uint_as_float(u[1].x & ~3u)) + (__uint_as_float(u[2].x & ~3u) + __uint_as_float(u[3].x & ~3u));
        float z1 = (__uint_as_float(u[0].y & ~3u) + __uint_as_float(u[1].y & ~3u)) + (__uint_as_float(u[2].y & ~3u) + __uint_as_float(u[3].y & ~3u));
#pragma unroll
        for (int o = 4; o <= 8; o <<= 1) { z0 += __shfl_xor_sync(~0u, z0, o); z1 += __shfl_xor_sync(~0u, z1, o); }
        if (lane < 8) st_rlx2(dst, tagf(z0, tag), tagf(z1, tag));
        TSA(5);
        uint4 w;
        spin = 0;
        do {
          w = ld_rlx(P.s->cs + 384 + 16 * bj + (lane & 15));
          bad = any_bad(w.x ^ tag);
        } while (bad && ++spin < SPIN_LIMIT);
        if (lane < 16) {
          uint32_t* d = reinterpret_cast<uint32_t*>(smem_raw + WBAR_OFF) + (lane >> 2) * 8 + (lane & 1) * 4 + ((lane >> 1) & 1);
          const float f0 = untag(w.x), f1 = __uint_as_float(w.y), f2 = __uint_as_float(w.z), f3 = __uint_as_float(w.w);
          const uint32_t h0 = pack(f0, f1), h1 = pack(f2, f3);
          d[0] = h0; d[2] = h1; d[40] = pack(f0 - blo(h0), f1 - bhi(h0)); d[42] = pack(f2 - blo(h1), f3 - bhi(h1));
        }
        __syncwarp();
        if (lane == 0) mbar_arrive(sb + BAR_AUXQ);
      }
      TSA(6);
    }
  } else {
    asm volatile("setmaxnreg.inc.sync.aligned.u32 224;");
    const uint32_t wg = warp >> 2, g = lane >> 2, t = lane & 3;
    uint32_t epoch = ld_rlx1(P.s->epoch + b * 8);
    const uint32_t l7 = lane & 7;
    const uint32_t frag_row = (l7 + 8 * ((lane >> 3) & 1)) * 128;
    const uint32_t frag_sw = (((uint32_t)lane >> 4) ^ l7) << 4;
    const uint32_t woff = warp * 2048 + frag_row;
    auto full_wait = [&](int n) { TSR(1 + 2 * wg, n); mbar_wait(sb + BAR_FULL + 8 * ring_pos(n), ring_par(n)); TSR(2 + 2 * wg, n); };
    auto release = [&](int n) { if (lane == 0) mbar_arrive(sb + BAR_EMPTY + 8 * ring_pos(n)); };
    uint32_t peer;
    asm("mapa.shared::cluster.u32 %0, %1, %2;" : "=r"(peer) : "r"(sb), "r"(br ^ 1));
    peer -= sb;
    const uint32_t dx = dlo(SB0, 16) + wg * 512;

    uint32_t wr[4][4], wb[4][4] = {};
    {
      const uint32_t* wp = reinterpret_cast<const uint32_t*>(P.pwphi + bj * 4 * 256) + g * 8 + t;
#pragma unroll
      for (int h = 0; h < 4; h++)
#pragma unroll
        for (int q = 0; q < 4; q++) wr[h][q] = __ldg(wp + h * 128 + (q & 1) * 64 + (q >> 1) * 4);
    }
    cta_sync();
    uint4* const rec = P.s->kv1 + ((bj * 17 + 2 * (warp ^ wg)) * 16 + bi) * 32;
    uint2* const zrec = reinterpret_cast<uint2*>(P.s->kv1 + ((bj * 17 + 16) * 16 + bi) * 32) + (warp ^ wg) * 8 + g;
    reinterpret_cast<uint32_t*>(smem_raw + ONES_OFF)[tid] = 0x3F803F80u;
    warm_wait(sb + BAR_X);
    pinu(epoch);
    const uint32_t tag = (epoch + 1) & 1;
    const Tag tg = {tag, 1 - P.always}, one = {1, tg.zero};
    const uint4* const csg = P.s->cs + 16 * bj + (lane & 15);
    auto cs_put = [&](uint4 v, const uint4* src, uint32_t off) {
      uint4 w[1] = {v};
      verify1(w, src, tg);
      sts4(sb + CS_OFF + off, w[0]);
      __syncwarp();
    };
    float mu0, mu1, rs0, rs1;
    float akv[96];
    uint4 cv;
    uint32_t a_p[4], a_f[4], a_r[2], a_v[2];
    uint32_t xr[16];
    {
      const uint2* xs = reinterpret_cast<const uint2*>(P.s->xs + 2 * (128 * bi + 16 * warp + g));
      uint2 st0, st1;
#pragma unroll
      for (int c = 0; c < 8; c++) {
        if (c > 0) mbar_wait(sb + BAR_X + 8 * c, 0);
        if (c == 0) TS(1);
        TSR(1 + 2 * wg, 48 + c);
        mbar_wait(sb + BAR_W + 8 * c, 0);
        TSR(2 + 2 * wg, 48 + c);
        wg_fence();
#pragma unroll
        for (int kk = 0; kk < 4; kk++) wgmma_n192_ss<H128, H128, 0, 1>(akv, dx + c * 1024 + kk * 2, dlo(SB0 + RING_OFF + (c & 3) * WSLOT + kk * 2048, 8192), (c | kk) != 0);
        wg_commit();
        if (c > 0) { wg_wait<1>(); if (c < 5 && lane == 0) mbar_arrive(sb + BAR_WE + 8 * (c - 1)); }
        if (c == 5 && P.always) {
#pragma unroll
          for (int h = 0; h < 4; h++)
#pragma unroll
            for (int q = 0; q < 4; q++) wb[h][q] = movm(wr[h][q]);
        }
        if (c == 1 && lane < 8) {
          st_rlx(P.s->o + (bi * 32 + bj * 4) * 256 + tid, 0, 0, 0, 0);
          st_rlx(P.s->h + (bi * 32 + bc * 4 + 3) * 256 + tid, 0, 0, 0, 0);
        }
        if (c == 1 && t == 0) st_rlx2(reinterpret_cast<uint2*>(P.s->mu + (bi * 8 + warp) * 32) + bj * 8 + g, tag ^ 1, tag ^ 1);
        if (c == 4) mbar_wait(sb + BAR_AUX, 0);
        if (c == 6) { st0 = ld_rlx2(xs); st1 = ld_rlx2(xs + 32); }
        if (c == 7) cv = ld_rlx(csg + 128 + (lane >> 4) * 128);
      }
      TS(23);
#pragma unroll
      for (int k = 0; k < 4; k++) {
        a_p[k] = sb + woff + (frag_sw ^ (k * 32));
        a_f[k] = sb + warp * 2048 + g * 128 + (t >> 1) * 16384 + (((((t & 1) * 4 + (t & 2)) ^ g) << 4) ^ (k << 4));
        pinu(a_p[k]); pinu(a_f[k]);
      }
#pragma unroll
      for (int k = 0; k < 2; k++) {
        a_r[k] = sb + warp * 2048 + g * 128 + (((2 * t + k) ^ g) << 4);
        a_v[k] = sb + V_OFF + warp * 2048 + (frag_row >> 1) + (((k * 2 + (lane >> 4)) ^ (l7 >> 1)) << 4);
        pinu(a_r[k]); pinu(a_v[k]);
      }
      verify2x2<256>(st0, st1, xs, tg);
      mu0 = untag(st0.x); rs0 = untag(st0.y); mu1 = untag(st1.x); rs1 = untag(st1.y);
      TS(24);
#pragma unroll
      for (int kk = 0; kk < 4; kk++) ldsm4(bc * 16384 + a_p[kk], xr[4 * kk], xr[4 * kk + 1], xr[4 * kk + 2], xr[4 * kk + 3]);
      cs_put(cv, csg + 128 + (lane >> 4) * 128, 256 + lane * 16);
      wg_wait<0>();
      pin(akv);
#pragma unroll
      for (int k = 0; k < 16; k++) pinu(xr[k]);
      if (lane == 0) mbar_arrive(sb + BAR_G);
    }
    TS(2);
    const float rl0 = rs0 * 1.4426950408889634f, rl1 = rs1 * 1.4426950408889634f;

    uint32_t pq[4][8];
    {
      float aq[32];
#pragma unroll
      for (int k = 0; k < 32; k++) aq[k] = akv[32 + k];
      uint32_t csp = sb + CS_OFF + (64 + 2 * t) * 4;
      uint4 cq;
#pragma unroll
      for (int it = 0; it < 2; it++) {
        const uint32_t tiles = it ? RING_OFF + 4 * SLOT : 0;
        {
          uint2 cs[8];
#pragma unroll
          for (int k = 0; k < 8; k++) cs[k] = lds2(csp + 32 * k);
#pragma unroll
          for (int h = 0; h < 4; h++) {
            uint32_t a[4];
#pragma unroll
            for (int q = 0; q < 4; q++) {
              const float m = (q & 1) ? mu1 : mu0;
              a[q] = pack(fmaf(-m, __uint_as_float(cs[2 * h + (q >> 1)].x), aq[8 * h + 2 * q]), fmaf(-m, __uint_as_float(cs[2 * h + (q >> 1)].y), aq[8 * h + 2 * q + 1]));
            }
            float p[8] = {};
            hmma(p[0], p[1], p[2], p[3], a[0], a[1], a[2], a[3], wb[h][0], wb[h][1]);
            hmma(p[4], p[5], p[6], p[7], a[0], a[1], a[2], a[3], wb[h][2], wb[h][3]);
            pq[h][0] = pack(p[0], p[1]); pq[h][1] = pack(p[2], p[3]); pq[h][2] = pack(p[4], p[5]); pq[h][3] = pack(p[6], p[7]);
          }
#pragma unroll
          for (int h = 0; h < 4; h++) stsm4(tiles + a_p[h], pq[h][0], pq[h][1], pq[h][2], pq[h][3]);
        }
        __syncwarp();
        uint4 pv[4];
#pragma unroll
        for (int k = 0; k < 4; k++) pv[k] = lds4(tiles + a_r[k & 1] + (k >> 1) * 1024);
        __syncwarp();
        float xf[16], arg[4], e[2][16], sum[2], inv, off[4];
        uint32_t vv[4], pk[4];
        uint2 cs[2];
        auto minmax = [&](int r) {
          const uint32_t w[8] = {pv[2 * r].x, pv[2 * r].y, pv[2 * r].z, pv[2 * r].w, pv[2 * r + 1].x, pv[2 * r + 1].y, pv[2 * r + 1].z, pv[2 * r + 1].w};
          const uint32_t x2 = max2(max2(max2(w[0], w[1]), max2(w[2], w[3])), max2(max2(w[4], w[5]), max2(w[6], w[7])));
          const uint32_t n2 = min2(min2(min2(w[0], w[1]), min2(w[2], w[3])), min2(min2(w[4], w[5]), min2(w[6], w[7])));
          const float rl = r ? rl1 : rl0;
          off[2 * r] = -rl * fmaxf(blo(x2), bhi(x2)); off[2 * r + 1] = rl * fminf(blo(n2), bhi(n2));
        };
        auto args = [&](int n) {
          const int u = n >> 2, q = n & 3;
          const float rl = (u >> 1) ? rl1 : rl0;
          if (!(u & 1)) {
            if (it == 0) {
              const uint32_t* w0 = &pv[(u >> 1) * 2].x + (q & 1) * 2;
              const uint32_t* w1 = &pv[(u >> 1) * 2 + 1].x + (q & 1) * 2;
              if (q < 2) { xf[4 * q] = blo(w0[0]); xf[4 * q + 1] = blo(w1[0]); xf[4 * q + 2] = blo(w0[1]); xf[4 * q + 3] = blo(w1[1]); }
              else { xf[4 * q] = bhi(w0[0]); xf[4 * q + 1] = bhi(w1[0]); xf[4 * q + 2] = bhi(w0[1]); xf[4 * q + 3] = bhi(w1[1]); }
            } else {
              const uint32_t* w = &pv[(u >> 1) * 2 + (q >> 1)].x + (q & 1) * 2;
              xf[4 * q] = blo(w[0]); xf[4 * q + 1] = bhi(w[0]); xf[4 * q + 2] = blo(w[1]); xf[4 * q + 3] = bhi(w[1]);
            }
          }
#pragma unroll
          for (int k = 0; k < 4; k++) arg[k] = fmaf(xf[4 * q + k], (u & 1) ? -rl : rl, off[u]);
        };
        minmax(0);
        args(0);
#pragma unroll
        for (int n = 0; n < 21; n++) {
          const int u = n >> 2, q = n & 3;
          if (n < 16) {
#pragma unroll
            for (int k = 0; k < 4; k++) { e[u & 1][4 * q + k] = ex2(arg[k]); pinf(e[u & 1][4 * q + k]); }
          }
          if (n < 15) { args(n + 1); pin(arg); }
          if (n >= 1 && n <= 16) {
            const float* f = e[((n - 1) >> 2) & 1] + 4 * ((n - 1) & 3);
            const float t4 = (f[0] + f[1]) + (f[2] + f[3]);
            float& sm = sum[((n - 1) >> 2) & 1];
            sm = ((n - 1) & 3) ? sm + t4 : t4;
            if (q == 2 && (u & 1)) sm = idle_pass(sm);
            if (q == 0) { inv = rcp(sm); inv = __uint_as_float(pack(inv, inv)); }
            pinf(q == 0 ? inv : sm);
          }
          if (n >= 5) {
            const int m = n - 5, um = m >> 2, qm = m & 3;
            const float* f = e[um & 1] + 4 * qm;
            const float iv = qm == 3 ? sum[um & 1] : inv;
            pk[2 * (qm & 1)] = mul2(pack(f[0], f[1]), __float_as_uint(iv)); pk[2 * (qm & 1) + 1] = mul2(pack(f[2], f[3]), __float_as_uint(iv));
            pinu(pk[2 * (qm & 1)]); pinu(pk[2 * (qm & 1) + 1]);
            if (qm == 2) sum[um & 1] = inv;
            if (qm & 1) sts4(tiles + a_f[(um & 1) * 2 + (qm >> 1)] + (um >> 1) * 1024, make_uint4(pk[0], pk[1], pk[2], pk[3]));
          }
          if (n == 2) { minmax(1); pin(off); }
          if (n == 10 && it == 0) cq = ld_rlx(csg);
          if (n < 16 && it == 0) {
            if (q == 0) { cs[0] = lds2(sb + CS_OFF + (128 + 2 * t) * 4 + 64 * u); cs[1] = lds2(sb + CS_OFF + (128 + 2 * t) * 4 + 64 * u + 32); }
            else {
#pragma unroll
              for (int k = (q == 1 ? 0 : q); k <= q; k++) {
                const float m = (k & 1) ? mu1 : mu0, r = (k & 1) ? rs1 : rs0;
                vv[k] = pack(fmaf(-m, __uint_as_float(cs[k >> 1].x), akv[64 + 8 * u + 2 * k]) * r, fmaf(-m, __uint_as_float(cs[k >> 1].y), akv[64 + 8 * u + 2 * k + 1]) * r);
                pinu(vv[k]);
              }
              if (q == 3) stsm4(a_v[u & 1] + (u >> 1) * 1024, vv[0], vv[1], vv[2], vv[3]);
            }
          }
        }
        if (it == 1) break;
        TS(26);
        fence_async();
        bar_sync(1, 256);
        TS(3);
        {
          float dkv[20];
          const uint32_t da = dlo(SB0, 8192) + wg * 1024, dw = wg * (64 - (64u << 16));
          wg_fence();
#pragma unroll
          for (int kk = 0; kk < 8; kk++)
            wgmma_n40_ss<H128, H64, 1, 1>(dkv, da + kk * 128, dlo(SB0 + V_OFF + kk * 2048, ONES_OFF - V_OFF - kk * 2048) + dw, kk != 0);
          wg_commit();
          const bool hl = (warp >> 1) & 1;
          cs_put(cq, csg, (lane & 15) * 16);
          wg_wait<0>();
          pin(dkv);
          TS(25);
#pragma unroll
          for (int nt = 0; nt < 2; nt++)
            st_rlx(rec + nt * (16 * 32) + lane, (__float_as_uint(hl ? dkv[8 + 4 * nt] : dkv[4 * nt]) & ~3u) | (tag + 1), __float_as_uint(hl ? dkv[10 + 4 * nt] : dkv[2 + 4 * nt]),
                   __float_as_uint(hl ? dkv[9 + 4 * nt] : dkv[1 + 4 * nt]), __float_as_uint(hl ? dkv[11 + 4 * nt] : dkv[3 + 4 * nt]));
          if (t == 0) st_rlx2(zrec, (__float_as_uint(dkv[16]) & ~3u) | (tag + 1), (__float_as_uint(dkv[18]) & ~3u) | (tag + 1));
          if (lane == 0) mbar_arrive(sb + BAR_STAGE);
        }
        TS(4);
        csp -= 256;
#pragma unroll
        for (int k = 0; k < 32; k++) aq[k] = akv[k];
        TS(5);
      }
      __syncwarp();
#pragma unroll
      for (int h = 0; h < 4; h++)
#pragma unroll
        for (int sg = 0; sg < 2; sg++)
          ldsm4(RING_OFF + (4 + (h >> 1)) * SLOT + a_p[(h & 1) * 2 + (sg ^ (h >> 1))], pq[h][4 * sg], pq[h][4 * sg + 1], pq[h][4 * sg + 2], pq[h][4 * sg + 3]);
    }
    TS(6);

    uint4 hf[3][4];
    uint32_t hres[16] = {};
    float s0 = 0.f, s1 = 0.f, ah[32], m0, m1;
    uint32_t hprobe = 0;
    {
      uint4 own[4], of[2][6];
      const uint32_t ktab = sb + TAB_OFF + t * 64 + g * 8;
      uint4* og = P.s->o + bi * 32 * 256 + tid;
      uint4* odst = og + bj * 1024;
      uint2* mup = reinterpret_cast<uint2*>(P.s->mu + (bi * 8 + warp) * 32) + g;
      uint2* mdst = mup + bj * 8;
      const uint2* msrc = mup + 16 * t;
      const uint4* psrc = og + ((bj + 2 + 2 * (lane & 3)) & 7) * 1024;
      const uint4* src[3];
#pragma unroll
      for (int m = 1; m < 4; m++) { src[m - 1] = og + ((bj + 2 * m) & 7) * 1024; pinp(src[m - 1]); }
      if (lane == 0) mbar_expect(sb + BAR_W + 8 * warp, 2048);
      asm volatile("barrier.cluster.wait.aligned;" ::: "memory");
      pinp(odst); pinp(mdst); pinp(msrc); pinp(psrc);
      mbar_wait(sb + BAR_WO, 0);
      {
        const uint4* ksrc = P.s->kv2 + bj * 320 + tid;
        const uint4* zsrc = P.s->kv2 + bj * 320 + 256 + (lane >> 1) * 4 + (lane & 1);
        uint4 v, w = make_uint4(tag, tag, tag, tag);
        int spin = 0;
        bool bad;
        do {
          v = ld_rlx(ksrc);
          if (warp == 7) asm volatile("ld.relaxed.gpu.global.v4.u32 {%0,%1,%2,%3}, [%4];" : "=r"(w.x), "=r"(w.y), "=r"(w.z), "=r"(w.w) : "l"(zsrc) : "memory");
          spin += idle_mma();
          bad = any_bad((v.x ^ tag) | bad2(w.x, w.y, tag) | bad2(w.z, w.w, tag));
        } while (bad && ++spin < SPIN_LIMIT);
        v.x &= ~1u;
        sts4(sb + TAB_OFF + tid * 16, v);
        if (warp == 7) asm volatile("st.shared.v2.u32 [%0], {%1, %2};" ::"r"(sb + TAB_OFF + 4096 + lane * 8), "r"(pack(untag(w.x), untag(w.y))), "r"(pack(untag(w.z), untag(w.w))) : "memory");
        bar_sync(1, 256);
        if (tid == 255) mbar_arrive(sb + BAR_KV);
      }
      if (wg == 1) bar_sync(10, 256);
      TS(7);
      uint2 kb[8][3], wm[4];
#pragma unroll
      for (int u = 0; u < 8; u++) { kb[u][2] = lds2(sb + TAB_OFF + 4096 + u * 32 + t * 8); kb[u][0] = lds2(ktab + u * 512); kb[u][1] = lds2(ktab + u * 512 + 256); }
#pragma unroll
      for (int h = 0; h < 4; h++) {
        float n[12] = {};
#pragma unroll
        for (int sg = 0; sg < 2; sg++) {
          const uint32_t* a = pq[h] + 4 * sg;
#pragma unroll
          for (int e = 2; e >= 0; e--) hmma(n[4 * e], n[4 * e + 1], n[4 * e + 2], n[4 * e + 3], a[0], a[1], a[2], a[3], kb[2 * h + sg][e].x, kb[2 * h + sg][e].y);
        }
        const float r0 = rcp(n[8] + 1e-6f), r1 = rcp(n[10] + 1e-6f);
        own[h] = make_uint4(pack(round_odd(n[0] * r0), n[1] * r0), pack(n[2] * r1, n[3] * r1), pack(n[4] * r0, n[5] * r0), pack(n[6] * r1, n[7] * r1));
        st_rlx(odst + h * 256, own[h].x, own[h].y, own[h].z, own[h].w);
      }
      uint32_t probe = 0;
      if (lane < 3) probe = ld_rlx1(reinterpret_cast<const unsigned*>(psrc));
      if (wg == 0) bar_arrive(10, 256);
      TS(8);
      float ap[32];
      mbar_wait(sb + BAR_AUXQ, 0);
      {
#pragma unroll
        for (int kk = 0; kk < 4; kk++) wm[kk] = lds2(sb + WBAR_OFF + (g & 1) * 160 + kk * 32 + t * 8);
        float mo[8] = {};
#pragma unroll
        for (int kk = 0; kk < 4; kk++) {
          hmma(mo[4 * (kk & 1)], mo[4 * (kk & 1) + 1], mo[4 * (kk & 1) + 2], mo[4 * (kk & 1) + 3], own[kk].x, own[kk].y, own[kk].z, own[kk].w, wm[kk].x, wm[kk].y);
        }
        if (t == 0) st_rlx2(mdst, tagf((mo[0] + mo[1]) + (mo[4] + mo[5]), tag), tagf((mo[2] + mo[3]) + (mo[6] + mo[7]), tag));
      }
#pragma unroll
      for (int k = 0; k < 16; k++) { ah[2 * k] = blo(xr[k]); ah[2 * k + 1] = bhi(xr[k]); }
      pin(ah);
      light_poll(psrc, lane < 3, one, probe);
      TS(9);
      if (wg == 1) bar_sync(8, 256);
#pragma unroll
      for (int k = 0; k < 12; k++) of[k / 6][k % 6] = ld_rlx(src[k % 3] + (k / 3) * 256);
      uint2 mv0 = ld_rlx2(msrc), mv1 = ld_rlx2(msrc + 8);
      if (wg == 0) bar_arrive(8, 256);
      wg_fence();
#pragma unroll
      for (int kk = 0; kk < 4; kk++) wgmma_n64_rs<H128, 1>(ap, own[kk].x, own[kk].y, own[kk].z, own[kk].w, dlo(SB0 + WO_OFF + kk * 2048, 8192), kk != 0);
#pragma unroll
      for (int kk = 0; kk < 4; kk++) wgmma_n64_rs<H128, 1>(ah, own[kk].x, own[kk].y, own[kk].z, own[kk].w, dlo(SB0 + WO_OFF + 32768 + kk * 2048, 8192), 1);
      wg_commit();
#pragma unroll
      for (int hf2 = 0; hf2 < 2; hf2++) {
        uint4(&f)[6] = of[hf2];
        if (hf2 == 0) verify6<0>(f, src, one); else verify6<8192>(f, src, one);
        TS(27 + hf2);
        wg_fence();
#pragma unroll
        for (int k = 0; k < 6; k++) wgmma_n64_rs<H128, 1>(ap, f[k].x, f[k].y, f[k].z, f[k].w, dlo(SB0 + WO_OFF + (k % 3 + 1) * 8192 + (2 * hf2 + k / 3) * 2048, 8192), 1);
        wg_commit();
        if (hf2 == 1) verify2x2<64>(mv0, mv1, msrc, tg);
        wg_fence();
#pragma unroll
        for (int k = 0; k < (hf2 ? 2 : 6); k++) wgmma_n64_rs<H128, 1>(ah, f[k].x, f[k].y, f[k].z, f[k].w, dlo(SB0 + WO_OFF + 32768 + (k % 3 + 1) * 8192 + (2 * hf2 + k / 3) * 2048, 8192), 1);
        wg_commit();
      }
      wg_wait<1>();
      pin(ap);
      const uint32_t abox = sb + V_OFF + warp * 2048 + lane * 16;
#pragma unroll
      for (int kk = 0; kk < 4; kk++) {
        const float* v = ap + 8 * kk;
        st_async4(peer + abox + kk * 512, pack(v[0], v[1]), pack(v[2], v[3]), pack(v[4], v[5]), pack(v[6], v[7]), peer + sb + BAR_W + 8 * warp);
      }
      TS(29);
      wg_fence();
#pragma unroll
      for (int k = 2; k < 6; k++) wgmma_n64_rs<H128, 1>(ah, of[1][k].x, of[1][k].y, of[1][k].z, of[1][k].w, dlo(SB0 + WO_OFF + 32768 + (k % 3 + 1) * 8192 + (2 + k / 3) * 2048, 8192), 1);
      wg_commit();
      uint4* hdst = P.s->h + (bi * 32 + bc * 4) * 256 + tid;
      pinp(hdst);
      full_wait(0);
      pinu(mv0.x); pinu(mv0.y);
      m0 = untag(mv0.x) + untag(mv1.x); m1 = untag(mv0.y) + untag(mv1.y);
#pragma unroll
      for (int o = 1; o <= 2; o <<= 1) { m0 += __shfl_xor_sync(~0u, m0, o); m1 += __shfl_xor_sync(~0u, m1, o); }
      m0 += mu0; m1 += mu1;
      wg_wait<0>();
      pin(ah);
      if (lane == 0) mbar_arrive(sb + BAR_WODONE);
#pragma unroll
      for (int k = 0; k < 16; k++) { const float m = (k & 1) ? m1 : m0; ah[2 * k] -= m; ah[2 * k + 1] -= m; }
      pin(ah);
      if (0) {
#pragma unroll
        for (int k = 0; k < 16; k++) { hres[k] = pack(ah[2 * k], ah[2 * k + 1]); pinu(hres[k]); }
        TS(30);
        mbar_wait_cluster(sb + BAR_W + 8 * warp, 1);
        TS(10);
#pragma unroll
        for (int kk = 0; kk < 4; kk++) hf[1][kk] = lds4(abox + kk * 512);
#pragma unroll
        for (int kk = 0; kk < 4; kk++) {
          hf[0][kk] = make_uint4(add2(hres[4 * kk], hf[1][kk].x) | 1u, add2(hres[4 * kk + 1], hf[1][kk].y), add2(hres[4 * kk + 2], hf[1][kk].z), add2(hres[4 * kk + 3], hf[1][kk].w));
          st_rlx(hdst + kk * 256, hf[0][kk].x, hf[0][kk].y, hf[0][kk].z, hf[0][kk].w);
        }
      } else {
      TS(30);
      mbar_wait_cluster(sb + BAR_W + 8 * warp, 1);
      TS(10);
      float xm[32];
#pragma unroll
      for (int kk = 0; kk < 4; kk++) {
        const uint4 v = lds4(abox + kk * 512);
        const uint32_t* w = &v.x;
#pragma unroll
        for (int q = 0; q < 4; q++) { xm[8 * kk + 2 * q] = blo(w[q]); xm[8 * kk + 2 * q + 1] = bhi(w[q]); }
      }
#pragma unroll
      for (int kk = 0; kk < 4; kk++) {
        float* dv = ah + 8 * kk;
#pragma unroll
        for (int k = 0; k < 8; k++) dv[k] += xm[8 * kk + k];
        hf[0][kk] = make_uint4(pack(round_odd(dv[0]), dv[1]), pack(dv[2], dv[3]), pack(dv[4], dv[5]), pack(dv[6], dv[7]));
        st_rlx(hdst + kk * 256, hf[0][kk].x, hf[0][kk].y, hf[0][kk].z, hf[0][kk].w);
      }
      }
    }
    TS(11);
    const uint32_t hn = sb + wg * 8192;

    uint32_t act[14][4];
    float r20, r21;
    uint2* ssp = reinterpret_cast<uint2*>(P.s->ss + (bi * 8 + warp) * 32) + g;
    {
      float acc[128];
      const uint4* hg = P.s->h + bi * 32 * 256 + tid;
#pragma unroll
      for (int c = 0; c < 8; c++) {
        uint4(&f)[4] = hf[c % 3];
        if (c > 0) verify4(f, hg + xperm(c) * 1024, one);
        if (c == 1) TS(12);
#pragma unroll
        for (int hh = 0; hh < 2; hh++) {
          const int s = 2 * c + hh;
          full_wait(s);
          wg_fence();
#pragma unroll
          for (int kk = 0; kk < 2; kk++)
            wgmma_n256_rs<H128, 1>(acc, f[2 * hh + kk].x, f[2 * hh + kk].y, f[2 * hh + kk].z, f[2 * hh + kk].w, dlo(dslot(s) + kk * 2048, 4096), (s | kk) != 0);
          wg_commit();
          if (s == 15) {
#pragma unroll
            for (int o = 1; o <= 2; o <<= 1) { s0 += __shfl_xor_sync(~0u, s0, o); s1 += __shfl_xor_sync(~0u, s1, o); }
            if (t == 0) st_rlx2(ssp + bj * 8, tagf(s0, tag), tagf(s1, tag));
          }
          if (s == 6) mbar_wait(sb + BAR_WODONE, 0);
          if (hh == 0) {
#pragma unroll
            for (int kk = 0; kk < 4; kk++) stsm4(c * 16384 + a_p[kk], f[kk].x, f[kk].y, f[kk].z, f[kk].w);
          }
          if (s == 1) {
            if (lane < 2) hprobe = ld_rlx1(reinterpret_cast<const unsigned*>(hg + xperm(1 + (lane & 1)) * 1024 + 768));
            if (P.always) {
#pragma unroll
              for (int k = 0; k < 16; k++) {
                const float m = (k & 1) ? m1 : m0;
                if (0) { const uint32_t w = (&hf[1][k >> 2].x)[k & 3]; ah[2 * k] += blo(w); ah[2 * k + 1] += bhi(w); }
                hres[k] = pack(ah[2 * k] + m, ah[2 * k + 1] + m);
                pinu(hres[k]);
                if (k & 1) s1 = fmaf(ah[2 * k], ah[2 * k], fmaf(ah[2 * k + 1], ah[2 * k + 1], s1));
                else s0 = fmaf(ah[2 * k], ah[2 * k], fmaf(ah[2 * k + 1], ah[2 * k + 1], s0));
              }
              pinf(s0); pinf(s1);
            }
            light_poll(hg + xperm(1 + (lane & 1)) * 1024 + 768, lane < 2, one, hprobe);
            ldn(hf[1], hg + xperm(1) * 1024);
            ldn(hf[2], hg + xperm(2) * 1024);
          }
          if (s > 0) { wg_wait<1>(); release(s - 1); }
          if (hh == 0 && c >= 1 && c + 2 < 8) ldn(hf[(c + 2) % 3], hg + xperm(c + 2) * 1024);
          if (s == 14) { fence_async(); bar_sync(6 + wg, 128); }
        }
      }
      wg_wait<0>();
      pin(acc);
      release(15);
      TS(13);
#pragma unroll
      for (int k = 0; k < 8; k++)
#pragma unroll
        for (int q = 0; q < 4; q++) {
          const int e = 8 * k + 2 * q;
          act[k][q] = reglu(acc[e], acc[e + 1], acc[64 + e], acc[64 + e + 1]);
          pinu(act[k][q]);
        }
    }
    TS(14);
    const uint32_t inbox = hn + (tid & 127) * 16;
    uint4 pa[14] = {};

    {
      float acc[96];
      uint2 sv0, sv1;
#pragma unroll
      for (int s = 0; s < 16; s++) {
        full_wait(16 + s);
        wg_fence();
#pragma unroll
        for (int kk = 0; kk < 2; kk++) wgmma_n192_ss<H128, H64, 0, 1>(acc, dx + (s >> 1) * 1024 + ((s & 1) * 2 + kk) * 2, dlo(dslot(16 + s) + kk * 1024, 2048), (s | kk) != 0);
        wg_commit();
        if (s == 6) mbar_wait_cluster(sb + BAR_PFREE + 8 * wg, 0);
        if (s == 14) mbar_wait_cluster(sb + BAR_PFREE2 + 8 * wg, 0);
        if (s >= 6 && s < 14) {
          const int k = s - 6;
          st_async4(peer + inbox + (k >> 2) * 16384 + (k & 3) * 2048, act[k][0], act[k][1], act[k][2], act[k][3], peer + sb + BAR_ACTA + 8 * wg);
        }
        if (s > 0) { wg_wait<1>(); release(16 + s - 1); }
        if (s == 9) { sv0 = ld_rlx2(ssp + 16 * t); sv1 = ld_rlx2(ssp + 16 * t + 8); }
        if (s == 12) {
          verify2x2<64>(sv0, sv1, ssp + 16 * t, tg);
          float q0 = untag(sv0.x) + untag(sv1.x), q1 = untag(sv0.y) + untag(sv1.y);
#pragma unroll
          for (int o = 1; o <= 2; o <<= 1) { q0 += __shfl_xor_sync(~0u, q0, o); q1 += __shfl_xor_sync(~0u, q1, o); }
          r20 = rcp(q0 * (1.f / DM) + 1e-5f); r21 = rcp(q1 * (1.f / DM) + 1e-5f);
        }
        if (s == 4 && lane == 0) mbar_arrive_remote(peer + sb + BAR_PFREE + 8 * wg);
        if (s == 8 && lane == 0) mbar_arrive_remote(peer + sb + BAR_PFREE2 + 8 * wg);
      }
      wg_wait<0>();
      pin(acc);
      release(31);
      TS(15);
#pragma unroll
      for (int k = 0; k < 6; k++)
#pragma unroll
        for (int q = 0; q < 4; q++) {
          const int e = 8 * k + 2 * q;
          act[8 + k][q] = reglu(acc[e], acc[e + 1], acc[48 + e], acc[48 + e + 1]);
          pinu(act[8 + k][q]);
        }
    }
    TS(16);

    {
      auto frag = [&](int f) {
        return f < 8 ? make_uint4(act[f < 8 ? f : 0][0], act[f < 8 ? f : 0][1], act[f < 8 ? f : 0][2], act[f < 8 ? f : 0][3])
             : f < 16 ? pa[f < 16 ? f - 8 : 0]
             : f < 22 ? make_uint4(act[f < 22 ? f - 8 : 0][0], act[f < 22 ? f - 8 : 0][1], act[f < 22 ? f - 8 : 0][2], act[f < 22 ? f - 8 : 0][3])
                      : pa[f - 14];
      };
      uint4* pg = P.s->part + bi * 8192 + tid;
      uint4* hg = P.s->h + bi * 8192 + tid;
      uint4* og = P.s->o + bi * 8192 + tid;
      uint4 in0[4], in1[4] = {}, in2[4] = {};
      uint32_t s12[16] = {}, m12 = 0;
      auto sum12 = [&]() {
        m12 = or3(or3(bad2(in2[0].x, in2[1].x, tag), bad2(in2[2].x, in2[3].x, tag), in1[0].x), or3(in1[1].x, in1[2].x, in1[3].x), 0);
#pragma unroll
        for (int k = 0; k < 16; k++) { s12[k] = add2((&in1[k >> 2].x)[k & 3], (k & 3) ? (&in2[k >> 2].x)[k & 3] : in2[k >> 2].x & ~1u); pinu(s12[k]); }
      };
      float a1[32], a2[32];
      if (wg == 1) bar_sync(9, 256);
#pragma unroll
      for (int u = 0; u < 32; u++) {
        const int tl = u >> 1, part = (int)((DOWN_PART >> (4 * tl)) & 3), ch = (int)((DOWN_CHUNK >> (4 * tl)) & 3);
        const int nk = part < 2 ? 4 : 3, f0 = (part < 2 ? 8 * part : 16 + 6 * (part - 2)) + (u & 1) * nk;
        const int n = tl < 6 ? 32 + tl : 28 + tl;
        const uint32_t base = (tl >= 6 && tl < 10) ? SB0 + (tl - 2) * 16384 : dslot(n);
        if ((u & 1) == 0) { if (tl >= 6 && tl < 10) mbar_wait(sb + BAR_X + 8 * (tl - 2), 1); else full_wait(n); }
        wg_fence();
#pragma unroll
        for (int kk = 0; kk < nk; kk++) {
          const uint4 a = frag(f0 + kk);
          const uint32_t d = dlo(base + ((u & 1) * nk + kk) * 2048, 8192);
          if ((ch & 1) == 0) wgmma_n64_rs<H128, 1>(a1, a.x, a.y, a.z, a.w, d, (f0 + kk) != 0);
          else wgmma_n64_rs<H128, 1>(a2, a.x, a.y, a.z, a.w, d, (f0 + kk) != 0);
        }
        wg_commit();
        if (u < 4) {
#pragma unroll
          for (int k = 8 + (u * 3) / 2; k < 8 + ((u + 1) * 3) / 2; k++)
            st_async4(peer + inbox + (k >> 2) * 16384 + (k & 3) * 2048, act[k][0], act[k][1], act[k][2], act[k][3], peer + sb + BAR_ACTB + 8 * wg);
        }
        if ((u & 1) == 0 && u > 0) { wg_wait<1>(); if (tl <= 6) release(32 + tl - 1); }
        if (u == 0) {
          mbar_wait_cluster(sb + BAR_ACTA + 8 * wg, 0);
#pragma unroll
          for (int k = 0; k < 8; k++) pa[k] = lds4(inbox + (k >> 2) * 16384 + (k & 3) * 2048);
        }
        if (u == 1 && wg == 0) bar_arrive(9, 256);
        if (u == 6) {
          mbar_wait_cluster(sb + BAR_ACTB + 8 * wg, 0);
#pragma unroll
          for (int k = 8; k < 14; k++) pa[k] = lds4(inbox + (k >> 2) * 16384 + (k & 3) * 2048);
        }
        const int sc = u >= 24 ? 2 : u >= 16 ? 1 : 0, su = u - (sc == 0 ? 10 : 8 + 8 * sc);
        if (su == 0) { if (sc & 1) pin(a2); else pin(a1); TS(17 + sc); }
        if (u != 24 || P.always)
#pragma unroll
        for (int k = 0; k < 4; k++)
          if (su == k >> sc) {
            const float* v = ((sc & 1) ? a2 : a1) + 8 * k;
            uint4* dst = sc == 2 ? og + bj * 1024 : sc == 1 ? hg + bc * 1024 : pg + bj * 1024;
            st_rlx(dst + k * 256, tagw(pack(v[0], v[1]), sc ? 0 : tag), pack(v[2], v[3]), pack(v[4], v[5]), pack(v[6], v[7]));
          }
        if (u == 28) ldn(in0, og + (bj ^ 2) * 1024);
        if (u == 20 || u == 23) {
#pragma unroll
          for (int k = 0; k < 4; k++)
            asm volatile("cp.async.cg.shared.global [%0], [%1], 16;" ::"r"(inbox + (u == 20 ? 16384 : 32768) + k * 2048), "l"((u == 20 ? pg + (bj ^ 6) * 1024 : hg + (bc ^ 2) * 1024) + k * 256) : "memory");
        }
        if (u == 27) {
          asm volatile("cp.async.wait_all;" ::: "memory");
#pragma unroll
          for (int k = 0; k < 4; k++) { in2[k] = lds4(inbox + 16384 + k * 2048); in1[k] = lds4(inbox + 32768 + k * 2048); }
        }
        if (u == 28 && P.always) sum12();
      }
      TS(31);
      uint32_t stg = hn + (warp & 3) * 2048;
      __nv_bfloat16* op = P.out + (128 * bi + 16 * warp + (lane >> 3)) * DM + 64 * bc + l7 * 8;
      uint32_t a_o[2] = {stg + (lane >> 3) * 128 + ((l7 ^ (lane >> 3)) << 4), stg + (lane >> 3) * 128 + 512 + ((l7 ^ (lane >> 3) ^ 4) << 4)};
      if (any_bad(or3(or3(in0[0].x, in0[1].x, in0[2].x), in0[3].x, m12))) {
        int spin = 0;
        do {
          const bool all = any_bad(m12);
          ldn(in0, og + (bj ^ 2) * 1024);
          if (all) { ldn(in2, pg + (bj ^ 6) * 1024); ldn(in1, hg + (bc ^ 2) * 1024); sum12(); }
        } while (any_bad(or3(or3(in0[0].x, in0[1].x, in0[2].x), in0[3].x, m12)) && ++spin < SPIN_LIMIT);
      }
      TS(20);
      float pre[32];
#pragma unroll
      for (int k = 0; k < 16; k++) {
        const uint32_t w = add2((&in0[k >> 2].x)[k & 3], s12[k]);
        if (1) s12[k] = w; else { pre[2 * k] = blo(w); pre[2 * k + 1] = bhi(w); }
      }
      wg_wait<0>();
      pin(a2);
      TS(21);
#pragma unroll
      for (int kk = 0; kk < 4; kk++) {
        uint32_t o[4];
#pragma unroll
        for (int q = 0; q < 4; q++) {
          const float r = (q & 1) ? r21 : r20;
          const int k = 4 * kk + q;
          if (1) asm("fma.rn.bf16x2 %0, %1, %2, %3;" : "=r"(o[q]) : "r"(s12[k]), "r"(pack(r, r)), "r"(pack(a2[2 * k] * r, a2[2 * k + 1] * r)));
          else o[q] = pack((a2[2 * k] + pre[2 * k]) * r, (a2[2 * k + 1] + pre[2 * k + 1]) * r);
          o[q] = add2(hres[k], o[q]);
        }
        stsm4(a_p[kk], o[0], o[1], o[2], o[3]);
      }
      __syncwarp();
#pragma unroll
      for (int k = 0; k < 4; k++) *reinterpret_cast<uint4*>(op + 4 * k * DM) = lds4(a_o[k & 1] + (k >> 1) * 1024);
      TS(22); TSG(1); TSDUMP;
    }
  }
}

typedef CUresult (*EncodeFn)(CUtensorMap*, CUtensorMapDataType, cuuint32_t, void*, const cuuint64_t*, const cuuint64_t*, const cuuint32_t*,
                             const cuuint32_t*, CUtensorMapInterleave, CUtensorMapSwizzle, CUtensorMapL2promotion, CUtensorMapFloatOOBfill);

void make_map(EncodeFn fn, CUtensorMap* m, const void* p, int rank, const cuuint64_t* dims, const cuuint64_t* strides, const cuuint32_t* box, CUtensorMapSwizzle sw) {
  const cuuint32_t es[3] = {1, 1, 1};
  CUresult r = fn(m, CU_TENSOR_MAP_DATA_TYPE_BFLOAT16, rank, const_cast<void*>(p), dims, strides, box, es, CU_TENSOR_MAP_INTERLEAVE_NONE, sw,
     CU_TENSOR_MAP_L2_PROMOTION_L2_128B, CU_TENSOR_MAP_FLOAT_OOB_FILL_NONE);
  (void)r;
}
void map2(EncodeFn fn, CUtensorMap* m, const void* p, int rows, int cols, int brows) {
  const cuuint64_t dims[2] = {(cuuint64_t)cols, (cuuint64_t)rows}, st[1] = {(cuuint64_t)cols * 2};
  const cuuint32_t box[2] = {64, (cuuint32_t)brows};
  make_map(fn, m, p, 2, dims, st, box, CU_TENSOR_MAP_SWIZZLE_128B);
}
void map3(EncodeFn fn, CUtensorMap* m, const void* p, int rows, int cols, int w, int nblk, int brows = 32) {
  const cuuint64_t dims[3] = {(cuuint64_t)w, (cuuint64_t)rows, (cuuint64_t)(cols / w)}, st[2] = {(cuuint64_t)cols * 2, (cuuint64_t)w * 2};
  const cuuint32_t box[3] = {(cuuint32_t)w, (cuuint32_t)brows, (cuuint32_t)nblk};
  make_map(fn, m, p, 3, dims, st, box, w == 64 ? CU_TENSOR_MAP_SWIZZLE_128B : CU_TENSOR_MAP_SWIZZLE_64B);
}

}

extern "C" void kernel_launch(void* const* d_in, const int* in_sizes, int n_in, void* d_out, int out_size) {
  (void)in_sizes; (void)n_in; (void)out_size;
  static EncodeFn fn = nullptr;
  static void* scratch = nullptr;
  if (!fn) {
    void* f = nullptr;
    cudaDriverEntryPointQueryResult qr;
    cudaGetDriverEntryPoint("cuTensorMapEncodeTiled", &f, cudaEnableDefault, &qr);
    fn = (EncodeFn)f;
    cudaGetSymbolAddress(&scratch, g_scratch);
    cudaFuncSetAttribute(fused_block_kernel, cudaFuncAttributeMaxDynamicSharedMemorySize, SMEM_BYTES);
  }
  Params P;
  P.px = (const __nv_bfloat16*)d_in[0]; P.pwqkv = (const __nv_bfloat16*)d_in[1]; P.pwphi = (const __nv_bfloat16*)d_in[2];
  P.pwo = (const __nv_bfloat16*)d_in[3]; P.pwg = (const __nv_bfloat16*)d_in[5]; P.pwu = (const __nv_bfloat16*)d_in[6];
  P.pwd = (const __nv_bfloat16*)d_in[7]; P.out = (__nv_bfloat16*)d_out;
  P.always = 1;
  P.s = (Scratch*)scratch;
  map2(fn, &P.x, P.px, SEQ, DM, 128);
  {
    const cuuint64_t dims[3] = {DM, DM, 3}, st[2] = {3 * DM * 2, DM * 2};
    const cuuint32_t box[3] = {64, 64, 3};
    make_map(fn, &P.wqkv, P.pwqkv, 3, dims, st, box, CU_TENSOR_MAP_SWIZZLE_128B);
  }
  map3(fn, &P.wsum, P.pwqkv, DM, 3 * DM, 64, 2, 64);
  map2(fn, &P.wo, P.pwo, DM, DM, 64);
  map3(fn, &P.wgA, P.pwg, DM, FF, 64, 2); map3(fn, &P.wuA, P.pwu, DM, FF, 64, 2);
  map3(fn, &P.wgB, P.pwg, DM, FF, 32, 3); map3(fn, &P.wuB, P.pwu, DM, FF, 32, 3);
  map2(fn, &P.wd128, P.pwd, FF, DM, 128); map2(fn, &P.wd96, P.pwd, FF, DM, 96);
  fused_block_kernel<<<132, 384, SMEM_BYTES>>>(P);
}
```
